```python
import torch

def _softmax(x, axis=-1):
    return torch.softmax(x, dim=axis)
def _gelu(x):
    return torch.nn.functional.gelu(x, approximate="tanh")
def _silu(x):
    return torch.nn.functional.silu(x)
def _sigmoid(x):
    return torch.sigmoid(x)
def _layernorm(x, axis=-1, eps=1e-5):
    m = x.mean(dim=axis, keepdim=True)
    v = x.var(dim=axis, keepdim=True, unbiased=False)
    return (x - m) / torch.sqrt(v + eps)
def _scatter_add(tgt, idx, src, axis=0):
    return tgt.clone().index_add_(axis, idx, src)
def _segment_sum(src, seg, n):
    out = torch.zeros((n,) + src.shape[1:], dtype=src.dtype)
    return out.index_add_(0, seg, src)
def _pad(x, pw):
    flat = tuple(v for pair in reversed(pw) for v in pair)
    return torch.nn.functional.pad(x, flat)

kernel_name = 'interleave_layers__spectral_gfnet__mixer_token_mlp__prompt'

def setup_inputs():

    _w = (lambda a: (lambda t: t.to(torch.bfloat16) if t.is_floating_point() else t)(torch.as_tensor(a)))
    def _A_setup():
        B, S, D = 1, 2048, 512
        Df = D // 2 + 1
        return {
            "x": _w((lambda *s: torch.randn(*s, dtype=torch.bfloat16) * 0.05)(B, S, D)),
            "w_r": _w((lambda *s: torch.randn(*s, dtype=torch.bfloat16) * 0.8)(S, Df) * 0.02),
            "w_i": _w((lambda *s: torch.randn(*s, dtype=torch.bfloat16) * 0.8)(S, Df) * 0.02),
        }
    _A_in = _A_setup()

    def _B_setup():
        B, S, D, F = 1, 2048, 512, 1792
        return {
            "x": _w((lambda *s: torch.randn(*s, dtype=torch.bfloat16) * 0.05)(B, S, D)),
            "w1": _w((lambda *s: torch.randn(*s, dtype=torch.bfloat16) * 0.4)(S, F) * (S ** -0.5)),
            "b1": _w((lambda *s: torch.randn(*s, dtype=torch.bfloat16) * 3.2)(F) * 0.02),
            "w2": _w((lambda *s: torch.randn(*s, dtype=torch.bfloat16) * 0.4)(F, S) * (F ** -0.5)),
            "b2": _w((lambda *s: torch.randn(*s, dtype=torch.bfloat16) * 1.6)(S) * 0.02),
        }
    _B_in = _B_setup()

    return {
        "A_x": _A_in["x"],
        "A_w_r": _A_in["w_r"],
        "A_w_i": _A_in["w_i"],
        "B_x": _B_in["x"],
        "B_w1": _B_in["w1"],
        "B_b1": _B_in["b1"],
        "B_w2": _B_in["w2"],
        "B_b2": _B_in["b2"],
    }

def reference(A_x, A_w_r, A_w_i, B_x, B_w1, B_b1, B_w2, B_b2):
    def _A_ref(x, w_r, w_i):
        B, S, D = x.shape
        X = (lambda x, axes=(-2,-1): torch.fft.rfft2(x.float(), dim=axes))(x, axes=(-2, -1))
        W = w_r + 1j * w_i
        X = X * W
        y = (lambda x, s, axes=(-2,-1): torch.fft.irfft2(x, s=s, dim=axes).to(torch.bfloat16))(X, (S, D), axes=(-2, -1))
        return y

    def _B_ref(x, w1, b1, w2, b2):
        B, S, D = x.shape
        h = _layernorm(x, axis=-1)
        u = torch.einsum("bsd,sf->bdf", h, w1) + b1
        u = _gelu(u)
        y = torch.einsum("bdf,fs->bds", u, w2) + b2
        return (lambda x, *d: x.permute(*d))(y, 0, 2, 1)

    x = A_x
    x = x + _A_ref(_layernorm(x, axis=-1), A_w_r, A_w_i)
    x = x + _B_ref(_layernorm(x, axis=-1), B_w1, B_b1, B_w2, B_b2)
    x = x + _A_ref(_layernorm(x, axis=-1), A_w_r, A_w_i)
    x = x + _B_ref(_layernorm(x, axis=-1), B_w1, B_b1, B_w2, B_b2)
    return x
```

```cpp
#include <cuda_runtime.h>
#include <cuda_bf16.h>
#include <cuda_fp16.h>
#include <cuda.h>
#include <stdint.h>

typedef __nv_bfloat16 bf16;

namespace {

constexpr int S_ = 2048, D_ = 512, F_ = 1792;

__device__ __align__(1024) uint32_t g_z1[128 * 4096];
__device__ __align__(1024) uint32_t g_z2[128 * 4096];
__device__ __align__(1024) bf16 g_x1[S_ * D_];
__device__ __align__(1024) bf16 g_h[S_ * D_];
__device__ __align__(1024) bf16 g_u[F_ * D_];
__device__ __align__(1024) bf16 g_x2[S_ * D_];
__device__ __align__(1024) uint2 g_wt[129 * 2048];
__device__ __align__(1024) float4 g_wt0[2048];
__device__ float g_wmax[64];

__device__ __forceinline__ uint32_t smem_u32(const void* p) { return (uint32_t)__cvta_generic_to_shared(p); }
__device__ __forceinline__ void griddep_wait() { asm volatile("griddepcontrol.wait;" ::: "memory"); }
__device__ __forceinline__ void griddep_launch() { asm volatile("griddepcontrol.launch_dependents;" ::: "memory"); }

__device__ __forceinline__ uint32_t pack_h2(float lo, float hi) {
    uint32_t r; asm("cvt.rn.f16x2.f32 %0, %1, %2;" : "=r"(r) : "f"(hi), "f"(lo)); return r;
}
__device__ __forceinline__ uint32_t pack_bf2(float lo, float hi) {
    uint32_t r; asm("cvt.rn.bf16x2.f32 %0, %1, %2;" : "=r"(r) : "f"(hi), "f"(lo)); return r;
}
__device__ __forceinline__ float bf_lo(uint32_t w) { return __uint_as_float(w << 16); }
__device__ __forceinline__ float bf_hi(uint32_t w) { return __uint_as_float(w & 0xffff0000u); }
__device__ __forceinline__ float bf16r(float x) { return __bfloat162float(__float2bfloat16_rn(x)); }

__device__ __forceinline__ void mma16816(float (&d)[4], const uint32_t (&a)[4], uint32_t b0, uint32_t b1) {
    asm("mma.sync.aligned.m16n8k16.row.col.f32.f16.f16.f32 {%0,%1,%2,%3}, {%4,%5,%6,%7}, {%8,%9}, {%0,%1,%2,%3};"
        : "+f"(d[0]), "+f"(d[1]), "+f"(d[2]), "+f"(d[3])
        : "r"(a[0]), "r"(a[1]), "r"(a[2]), "r"(a[3]), "r"(b0), "r"(b1));
}

__device__ __forceinline__ void mbar_init(uint32_t bar, int cnt) {
    asm volatile("mbarrier.init.shared::cta.b64 [%0], %1;" ::"r"(bar), "r"(cnt) : "memory");
}
__device__ __forceinline__ void mbar_expect_tx(uint32_t bar, uint32_t bytes) {
    asm volatile("mbarrier.arrive.expect_tx.shared::cta.b64 _, [%0], %1;" ::"r"(bar), "r"(bytes) : "memory");
}
__device__ __forceinline__ void mbar_arrive(uint32_t bar) {
    asm volatile("mbarrier.arrive.shared::cta.b64 _, [%0];" ::"r"(bar) : "memory");
}
__device__ __forceinline__ void mbar_wait(uint32_t bar, uint32_t parity) {
    asm volatile(
        "{\n.reg .pred p;\n"
        "WL_%=:\n"
        "mbarrier.try_wait.parity.shared::cta.b64 p, [%0], %1;\n"
        "@p bra WD_%=;\n"
        "bra WL_%=;\n"
        "WD_%=:\n}" ::"r"(bar), "r"(parity) : "memory");
}

struct Trig16 {
    float c, s;
    __device__ __forceinline__ Trig16(int lane) {
        float x = (float)(lane & 15) * 0.125f;
        sincospif(x, &s, &c);
        c *= 0.25f; s *= 0.25f;
    }
    __device__ __forceinline__ float C(int i) const { return __shfl_sync(0xffffffffu, c, i & 15); }
    __device__ __forceinline__ float Sn(int i) const { return __shfl_sync(0xffffffffu, s, i & 15); }
};
__device__ __forceinline__ int perm_pi(int m) { return 2 * (m & 7) + (m >> 3); }
__device__ __forceinline__ int perm_p1(int m) { return ((m >> 1) & 3) + 4 * (m & 1) + (m & 8); }

__device__ __forceinline__ void stage_inter(const uint32_t (&Are)[2][4], const uint32_t (&Aim)[2][4],
                                            const uint32_t (&B)[4][2],
                                            float (&Cre)[2][4], float (&Cim)[2][4]) {
#pragma unroll
    for (int jn = 0; jn < 2; jn++) {
#pragma unroll
        for (int q = 0; q < 4; q++) { Cre[jn][q] = 0.f; Cim[jn][q] = 0.f; }
#pragma unroll
        for (int ks = 0; ks < 2; ks++) {
            mma16816(Cre[jn], Are[ks], B[2 * ks][jn], B[2 * ks + 1][jn]);
            mma16816(Cim[jn], Aim[ks], B[2 * ks][jn], B[2 * ks + 1][jn]);
        }
    }
}
__device__ __forceinline__ void stage_c2b(const uint32_t (&Fc)[4], const uint32_t (&F1)[4], const uint32_t (&F2)[4],
                                          const float (&Cre)[2][4], const float (&Cim)[2][4],
                                          float (&Ore)[2][4], float (&Oim)[2][4]) {
#pragma unroll
    for (int j = 0; j < 2; j++) {
        uint32_t r0 = pack_h2(Cre[0][2 * j], Cre[0][2 * j + 1]), r1 = pack_h2(Cre[1][2 * j], Cre[1][2 * j + 1]);
        uint32_t i0 = pack_h2(Cim[0][2 * j], Cim[0][2 * j + 1]), i1 = pack_h2(Cim[1][2 * j], Cim[1][2 * j + 1]);
#pragma unroll
        for (int q = 0; q < 4; q++) { Ore[j][q] = 0.f; Oim[j][q] = 0.f; }
        mma16816(Ore[j], Fc, r0, r1);
        mma16816(Oim[j], Fc, i0, i1);
        mma16816(Ore[j], F1, i0, i1);
        mma16816(Oim[j], F2, r0, r1);
    }
}
__device__ __forceinline__ void stage_c2a(const uint32_t (&Fc)[4], const uint32_t (&F1)[4], const uint32_t (&F2)[4],
                                          const float (&Cre)[2][4], const float (&Cim)[2][4],
                                          float (&Ore)[2][4], float (&Oim)[2][4]) {
    uint32_t ar[4], ai[4];
    ar[0] = pack_h2(Cre[0][0], Cre[0][1]); ar[1] = pack_h2(Cre[0][2], Cre[0][3]);
    ar[2] = pack_h2(Cre[1][0], Cre[1][1]); ar[3] = pack_h2(Cre[1][2], Cre[1][3]);
    ai[0] = pack_h2(Cim[0][0], Cim[0][1]); ai[1] = pack_h2(Cim[0][2], Cim[0][3]);
    ai[2] = pack_h2(Cim[1][0], Cim[1][1]); ai[3] = pack_h2(Cim[1][2], Cim[1][3]);
#pragma unroll
    for (int j = 0; j < 2; j++) {
#pragma unroll
        for (int q = 0; q < 4; q++) { Ore[j][q] = 0.f; Oim[j][q] = 0.f; }
        mma16816(Ore[j], ar, Fc[j], Fc[j + 2]);
        mma16816(Oim[j], ai, Fc[j], Fc[j + 2]);
        mma16816(Ore[j], ai, F1[j], F1[j + 2]);
        mma16816(Oim[j], ar, F2[j], F2[j + 2]);
    }
}

__device__ __forceinline__ void warp_ln2(float (&v)[2][16]) {
    float s1[2], s2[2], piv[2];
#pragma unroll
    for (int k = 0; k < 2; k++) {
        piv[k] = __shfl_sync(0xffffffffu, v[k][0], 0);
        float a = 0.f, b = 0.f;
#pragma unroll
        for (int i = 0; i < 16; i++) { float d = v[k][i] - piv[k]; a += d; b = fmaf(d, d, b); }
        s1[k] = a; s2[k] = b;
    }
#pragma unroll
    for (int o = 16; o > 0; o >>= 1) {
#pragma unroll
        for (int k = 0; k < 2; k++) {
            s1[k] += __shfl_xor_sync(0xffffffffu, s1[k], o);
            s2[k] += __shfl_xor_sync(0xffffffffu, s2[k], o);
        }
    }
#pragma unroll
    for (int k = 0; k < 2; k++) {
        float md = s1[k] * (1.f / 512.f);
        float var = fmaxf(s2[k] * (1.f / 512.f) - md * md, 0.f);
        float mean = bf16r(piv[k] + md);
        float den = bf16r(sqrtf(bf16r(bf16r(var) + 1e-5f)));
        float rd = 1.0f / den;
#pragma unroll
        for (int i = 0; i < 16; i++) v[k][i] = bf16r(bf16r(v[k][i] - mean) * rd);
    }
}

__device__ __forceinline__ float wscale_exp(int lane, float& inv) {
    float m = fmaxf(g_wmax[lane], g_wmax[lane + 32]);
#pragma unroll
    for (int o = 16; o > 0; o >>= 1) m = fmaxf(m, __shfl_xor_sync(0xffffffffu, m, o));
    int e = (int)((__float_as_uint(m) >> 23) & 0xff);
    e = min(max(e, 2), 250);
    inv = __uint_as_float((uint32_t)(e + 1) << 23);
    return __uint_as_float((uint32_t)(253 - e) << 23);
}

__device__ void wprep(const bf16* __restrict__ wr, const bf16* __restrict__ wi, int q, uint16_t* sm) {
    const int tid = threadIdx.x, lane = tid & 31, w = tid >> 5;
    const int c = q >> 3, g = q & 7;
    const uint16_t* pr = (const uint16_t*)wr;
    const uint16_t* pi = (const uint16_t*)wi;
    float mx = 0.f;
#pragma unroll
    for (int it = 0; it < 4; it++) {
        int rr = w * 4 + it;
        int t = rr >> 3, idx = rr & 7;
        int jp = idx >> 2, h = (idx >> 1) & 1, r = idx & 1;
        int k1 = c + 8 * ((2 * g + h) + 16 * (4 * t + 2 * r + jp));
        int nk1 = (2048 - k1) & 2047;
        const uint16_t* ar = pr + k1 * 257; const uint16_t* ai = pi + k1 * 257;
        const uint16_t* br = pr + nk1 * 257; const uint16_t* bi = pi + nk1 * 257;
#pragma unroll
        for (int u = 0; u < 5; u++) {
            int j = u * 32 + lane;
            if (j <= 128) {
                uint16_t v0 = ar[j], v1 = ai[j], v2 = br[256 - j], v3 = bi[256 - j];
                sm[(0 * 32 + rr) * 132 + j] = v0;
                sm[(1 * 32 + rr) * 132 + j] = v1;
                sm[(2 * 32 + rr) * 132 + j] = v2;
                sm[(3 * 32 + rr) * 132 + j] = v3;
                mx = fmaxf(mx, fmaxf(fmaxf(fabsf(bf_lo(v0)), fabsf(bf_lo(v1))), fmaxf(fabsf(bf_lo(v2)), fabsf(bf_lo(v3)))));
            }
        }
        if (lane == 0) {
            float a_re = 0.5f * (bf_lo(ar[0]) + bf_lo(br[0]));
            float a_im = 0.5f * (bf_lo(ai[0]) - bf_lo(bi[0]));
            float b_re = 0.5f * (bf_lo(ar[256]) + bf_lo(br[256]));
            float b_im = 0.5f * (bf_lo(ai[256]) - bf_lo(bi[256]));
            g_wt0[c * 256 + g * 32 + rr] = make_float4(a_re, a_im, b_re, b_im);
        }
    }
#pragma unroll
    for (int o = 16; o > 0; o >>= 1) mx = fmaxf(mx, __shfl_xor_sync(0xffffffffu, mx, o));
    __shared__ float smx[8];
    if (lane == 0) smx[w] = mx;
    __syncthreads();
    if (tid == 0) {
        float m = smx[0];
#pragma unroll
        for (int i = 1; i < 8; i++) m = fmaxf(m, smx[i]);
        g_wmax[q] = m;
    }
    for (int j = w; j <= 128; j += 8) {
        uint32_t a = (uint32_t)sm[(0 * 32 + lane) * 132 + j] | ((uint32_t)sm[(1 * 32 + lane) * 132 + j] << 16);
        uint32_t b = (uint32_t)sm[(2 * 32 + lane) * 132 + j] | ((uint32_t)(sm[(3 * 32 + lane) * 132 + j] ^ 0x8000u) << 16);
        g_wt[j * 2048 + c * 256 + g * 32 + lane] = make_uint2(a, b);
    }
}

__global__ void __launch_bounds__(256) k_p1(const bf16* __restrict__ x, const bf16* __restrict__ wr,
                                            const bf16* __restrict__ wi) {
    __shared__ __align__(16) uint32_t stage[4 * 32 * 132 / 2];
    if (blockIdx.x >= 128) {
        griddep_launch();
        wprep(wr, wi, blockIdx.x - 128, (uint16_t*)stage);
        return;
    }
    const int lane = threadIdx.x & 31, w = threadIdx.x >> 5, g = lane >> 2, t = lane & 3;
    Trig16 tg(lane);
    uint32_t Are[2][4], Aim[2][4], Fc[4], Fs[4], Fn[4];
#pragma unroll
    for (int ks = 0; ks < 2; ks++)
#pragma unroll
        for (int r = 0; r < 4; r++) {
            int idx = (8 * ks + t + 4 * (r >> 1)) * perm_p1(g + 8 * (r & 1));
            float c = tg.C(idx), s = tg.Sn(idx);
            Are[ks][r] = pack_h2(c, s); Aim[ks][r] = pack_h2(-s, c);
        }
#pragma unroll
    for (int r = 0; r < 4; r++) {
        int e = g + 8 * (r & 1), k0 = 2 * t + 8 * (r >> 1);
        int i0 = e * perm_pi(k0), i1 = e * perm_pi(k0 + 1);
        float c0 = tg.C(i0), c1 = tg.C(i1), s0 = tg.Sn(i0), s1 = tg.Sn(i1);
        Fc[r] = pack_h2(c0, c1); Fs[r] = pack_h2(s0, s1); Fn[r] = pack_h2(-s0, -s1);
    }
    float twc[2][4], tws[2][4];
#pragma unroll
    for (int jn = 0; jn < 2; jn++)
#pragma unroll
        for (int q = 0; q < 4; q++) {
            int c = perm_p1(g + 8 * (q >> 1)), b = 4 * t + 2 * (q & 1) + jn;
            sincospif((float)(b * c) * (1.f / 128.f), &tws[jn][q], &twc[jn][q]);
        }
    griddep_wait();
    griddep_launch();

    const uint2* row = (const uint2*)(x + (size_t)(blockIdx.x * 16 + 2 * w) * 512);
    uint2 raw[2][4];
#pragma unroll
    for (int k = 0; k < 2; k++)
#pragma unroll
        for (int i = 0; i < 4; i++) raw[k][i] = row[k * 128 + 8 * (t + 4 * i) + g];
    float v[2][16];
#pragma unroll
    for (int k = 0; k < 2; k++)
#pragma unroll
        for (int i = 0; i < 4; i++) {
            v[k][4 * i + 0] = bf_lo(raw[k][i].x); v[k][4 * i + 1] = bf_hi(raw[k][i].x);
            v[k][4 * i + 2] = bf_lo(raw[k][i].y); v[k][4 * i + 3] = bf_hi(raw[k][i].y);
        }
    warp_ln2(v);
    uint32_t outw[2][8];
#pragma unroll
    for (int k = 0; k < 2; k++) {
        uint32_t B[4][2];
#pragma unroll
        for (int i = 0; i < 4; i++) {
            B[i][0] = pack_h2(v[k][4 * i], v[k][4 * i + 1]);
            B[i][1] = pack_h2(v[k][4 * i + 2], v[k][4 * i + 3]);
        }
        float Cre[2][4], Cim[2][4], Ore[2][4], Oim[2][4];
        stage_inter(Are, Aim, B, Cre, Cim);
#pragma unroll
        for (int jn = 0; jn < 2; jn++)
#pragma unroll
            for (int q = 0; q < 4; q++) {
                float re = Cre[jn][q], im = Cim[jn][q];
                Cre[jn][q] = re * twc[jn][q] + im * tws[jn][q];
                Cim[jn][q] = im * twc[jn][q] - re * tws[jn][q];
            }
        stage_c2b(Fc, Fs, Fn, Cre, Cim, Ore, Oim);
#pragma unroll
        for (int j = 0; j < 2; j++)
#pragma unroll
            for (int q = 0; q < 4; q++) outw[k][4 * j + q] = pack_h2(Ore[j][q], Oim[j][q]);
    }
    const int f = (t >> 1) | ((g & 3) << 1);
#pragma unroll
    for (int j = 0; j < 2; j++)
#pragma unroll
        for (int q = 0; q < 4; q++) {
            int k = (t + 4 * (q & 1) + 8 * j) + 16 * (g + 8 * (q >> 1));
            *(uint2*)&stage[k * 16 + 2 * (w ^ f)] = make_uint2(outw[0][4 * j + q], outw[1][4 * j + q]);
        }
    __syncthreads();
    uint4* dst = (uint4*)(g_z1 + (size_t)blockIdx.x * 4096);
#pragma unroll
    for (int i = 0; i < 4; i++) dst[threadIdx.x + 256 * i] = ((const uint4*)stage)[threadIdx.x + 256 * i];
}

__device__ __forceinline__ int swz_f(int k) { return ((k >> 1) & 1) | (((k >> 4) & 3) << 1); }

__global__ void __launch_bounds__(256) k_p2() {
    __shared__ __align__(16) uint32_t XB[2 * 8 * 416];
    const int lane = threadIdx.x & 31, w = threadIdx.x >> 5, g = lane >> 2, t = lane & 3;
    const int j = blockIdx.x;
    const int kc[2] = {j, (256 - j) & 255};
    const int fc[2] = {swz_f(kc[0]), swz_f(kc[1])};
    Trig16 tg(lane);
    uint32_t M8[2][4], M8i[2][4];
#pragma unroll
    for (int r = 0; r < 4; r++) {
        int idx = 2 * g * (t + 4 * (r >> 1));
        float c = tg.C(idx), s = tg.Sn(idx);
        if ((r & 1) == 0) {
            M8[0][r] = pack_h2(2.f * c, 2.f * s); M8[1][r] = pack_h2(2.f * c, -2.f * s);
            M8i[0][r] = pack_h2(c, -s); M8i[1][r] = pack_h2(c, -s);
        } else {
            M8[0][r] = pack_h2(-2.f * s, 2.f * c); M8[1][r] = pack_h2(-2.f * s, -2.f * c);
            M8i[0][r] = pack_h2(s, c); M8i[1][r] = pack_h2(-s, -c);
        }
    }
    uint32_t Are[2][4], Aim[2][4], Fc[4], Fs[4], Fn[4];
#pragma unroll
    for (int ks = 0; ks < 2; ks++)
#pragma unroll
        for (int r = 0; r < 4; r++) {
            int idx = (8 * ks + t + 4 * (r >> 1)) * perm_pi(g + 8 * (r & 1));
            float c = tg.C(idx), s = tg.Sn(idx);
            Are[ks][r] = pack_h2(c, s); Aim[ks][r] = pack_h2(-s, c);
        }
#pragma unroll
    for (int r = 0; r < 4; r++) {
        int e = perm_pi(g + 8 * (r & 1)), k0 = 2 * t + 8 * (r >> 1);
        int i0 = e * perm_pi(k0), i1 = e * perm_pi(k0 + 1);
        float c0 = tg.C(i0), c1 = tg.C(i1), s0 = tg.Sn(i0), s1 = tg.Sn(i1);
        Fc[r] = pack_h2(c0, c1); Fs[r] = pack_h2(s0, s1); Fn[r] = pack_h2(-s0, -s1);
    }
    float twc[2][4], tws[2][4];
    float tac[2][4], tas[2][4];
    float tbc[2][4], tbs[2][4];
#pragma unroll
    for (int a = 0; a < 2; a++)
#pragma unroll
        for (int q = 0; q < 4; q++) {
            int e0 = 2 * g + (q >> 1), b0 = 4 * t + 2 * (q & 1) + a;
            sincospif((float)(e0 * b0) * (1.f / 128.f), &tws[a][q], &twc[a][q]);
            int b = 16 * (2 * w + a) + 4 * t + q;
            sincospif((float)(b * g) * (1.f / 1024.f), &tas[a][q], &tac[a][q]);
            int bb = 16 * (2 * g + a) + 4 * t + q;
            sincospif((float)(bb * w) * (1.f / 1024.f), &tbs[a][q], &tbc[a][q]);
        }
    float sth, cth;
    sincospif((float)j * (1.f / 256.f), &sth, &cth);

    griddep_wait();
    griddep_launch();

    uint2 zin[2][2][2];
#pragma unroll
    for (int col = 0; col < 2; col++)
#pragma unroll
        for (int be = 0; be < 2; be++)
#pragma unroll
            for (int ar = 0; ar < 2; ar++) {
                int sblk = 16 * (t + 4 * ar) + 2 * w + be;
                zin[col][be][ar] = *(const uint2*)&g_z1[(size_t)sblk * 4096 + kc[col] * 16 + 2 * (g ^ fc[col])];
            }
    float wa[8][4];
    if (j == 0) {
#pragma unroll
        for (int i = 0; i < 8; i++) {
            float4 q4 = g_wt0[w * 256 + lane * 8 + i];
            wa[i][0] = q4.x; wa[i][1] = q4.y; wa[i][2] = q4.z; wa[i][3] = q4.w;
        }
    } else {
        const uint4* wp = (const uint4*)&g_wt[(size_t)j * 2048 + w * 256 + lane * 8];
#pragma unroll
        for (int i = 0; i < 4; i++) {
            uint4 q4 = wp[i];
            wa[2 * i][0] = bf_lo(q4.x); wa[2 * i][1] = bf_hi(q4.x); wa[2 * i][2] = bf_lo(q4.y); wa[2 * i][3] = bf_hi(q4.y);
            wa[2 * i + 1][0] = bf_lo(q4.z); wa[2 * i + 1][1] = bf_hi(q4.z); wa[2 * i + 1][2] = bf_lo(q4.w); wa[2 * i + 1][3] = bf_hi(q4.w);
        }
    }
    float winv;
    const float hs = 0.5f * wscale_exp(lane, winv);

#pragma unroll
    for (int col = 0; col < 2; col++)
#pragma unroll
        for (int be = 0; be < 2; be++) {
            float C0[4] = {0.f, 0.f, 0.f, 0.f}, C1[4] = {0.f, 0.f, 0.f, 0.f};
            mma16816(C0, M8[col], zin[col][be][0].x, zin[col][be][1].x);
            mma16816(C1, M8[col], zin[col][be][0].y, zin[col][be][1].y);
            uint32_t o[4];
#pragma unroll
            for (int i = 0; i < 4; i++) {
                float re = (i & 1) ? C1[i >> 1] : C0[i >> 1];
                float im = (i & 1) ? C1[2 + (i >> 1)] : C0[2 + (i >> 1)];
                o[i] = pack_h2(re * tac[be][i] + im * tas[be][i], im * tac[be][i] - re * tas[be][i]);
            }
            *(uint4*)&XB[col * 3328 + g * 416 + 16 * (g & 1) + (2 * w + be) * 24 + 4 * t] = make_uint4(o[0], o[1], o[2], o[3]);
        }
    __syncthreads();

    float Ure[2][2][4], Uim[2][2][4];
#pragma unroll
    for (int col = 0; col < 2; col++) {
        uint32_t B[4][2];
#pragma unroll
        for (int i = 0; i < 4; i++) {
            uint2 q2 = *(const uint2*)&XB[col * 3328 + w * 416 + 16 * (w & 1) + (t + 4 * i) * 24 + 2 * g];
            B[i][0] = q2.x; B[i][1] = q2.y;
        }
        float Cre[2][4], Cim[2][4];
        stage_inter(Are, Aim, B, Cre, Cim);
#pragma unroll
        for (int jn = 0; jn < 2; jn++)
#pragma unroll
            for (int q = 0; q < 4; q++) {
                float re = Cre[jn][q], im = Cim[jn][q];
                Cre[jn][q] = re * twc[jn][q] + im * tws[jn][q];
                Cim[jn][q] = im * twc[jn][q] - re * tws[jn][q];
            }
        stage_c2a(Fc, Fs, Fn, Cre, Cim, Ure[col], Uim[col]);
    }
#pragma unroll
    for (int jp = 0; jp < 2; jp++)
#pragma unroll
        for (int q = 0; q < 4; q++) {
            const float* p = wa[4 * jp + q];
            float sr = (p[0] + p[2]) * hs, si = (p[1] + p[3]) * hs;
            float dr = (p[0] - p[2]) * hs, di = (p[1] - p[3]) * hs;
            float a1r = sr - sth * dr, a1i = si - sth * di;
            float a2r = sr + sth * dr, a2i = si + sth * di;
            float br = -cth * di, bi = cth * dr;
            float ur = Ure[0][jp][q], ui = Uim[0][jp][q], vr = Ure[1][jp][q], vi = Uim[1][jp][q];
            Ure[0][jp][q] = a1r * ur - a1i * ui + br * vr - bi * vi;
            Uim[0][jp][q] = a1r * ui + a1i * ur + br * vi + bi * vr;
            Ure[1][jp][q] = a2r * vr - a2i * vi - br * ur + bi * ui;
            Uim[1][jp][q] = a2r * vi + a2i * vr - br * ui - bi * ur;
        }
#pragma unroll
    for (int col = 0; col < 2; col++) {
        float Cre[2][4], Cim[2][4], Ore[2][4], Oim[2][4];
        stage_c2b(Fc, Fn, Fs, Ure[col], Uim[col], Cre, Cim);
#pragma unroll
        for (int jn = 0; jn < 2; jn++)
#pragma unroll
            for (int q = 0; q < 4; q++) {
                float re = Cre[jn][q], im = Cim[jn][q];
                Cre[jn][q] = re * twc[jn][q] - im * tws[jn][q];
                Cim[jn][q] = im * twc[jn][q] + re * tws[jn][q];
            }
        stage_c2b(Fc, Fn, Fs, Cre, Cim, Ore, Oim);
#pragma unroll
        for (int h = 0; h < 2; h++) {
            uint32_t o[4];
#pragma unroll
            for (int i = 0; i < 4; i++) {
                float re = Ore[i & 1][2 * h + (i >> 1)], im = Oim[i & 1][2 * h + (i >> 1)];
                o[i] = pack_h2(re * tbc[h][i] - im * tbs[h][i], im * tbc[h][i] + re * tbs[h][i]);
            }
            *(uint4*)&XB[col * 3328 + w * 416 + 8 * (w & 3) + (2 * g + h) * 24 + 4 * t] = make_uint4(o[0], o[1], o[2], o[3]);
        }
    }
    __syncthreads();
#pragma unroll
    for (int col = 0; col < 2; col++) {
        if (col == 1 && kc[0] == kc[1]) break;
#pragma unroll
        for (int be = 0; be < 2; be++) {
            uint2 q0 = *(const uint2*)&XB[col * 3328 + t * 416 + 8 * t + (2 * w + be) * 24 + 2 * g];
            uint2 q1 = *(const uint2*)&XB[col * 3328 + (t + 4) * 416 + 8 * t + (2 * w + be) * 24 + 2 * g];
            float C0[4] = {0.f, 0.f, 0.f, 0.f}, C1[4] = {0.f, 0.f, 0.f, 0.f};
            mma16816(C0, M8i[col], q0.x, q1.x);
            mma16816(C1, M8i[col], q0.y, q1.y);
            uint32_t o0 = pack_h2(C0[0], C0[2]), o1 = pack_h2(C1[0], C1[2]);
            uint32_t o2 = pack_h2(C0[1], C0[3]), o3 = pack_h2(C1[1], C1[3]);
            uint4 ov = (fc[col] & 1) ? make_uint4(o2, o3, o0, o1) : make_uint4(o0, o1, o2, o3);
            int sblk = 16 * g + 2 * w + be;
            *(uint4*)&g_z2[(size_t)sblk * 4096 + kc[col] * 16 + 4 * (t ^ (fc[col] >> 1))] = ov;
        }
    }
}

__global__ void __launch_bounds__(256) k_p3(const bf16* __restrict__ x) {
    __shared__ __align__(128) uint32_t buf[4096];
    __shared__ __align__(8) uint64_t bar;
    const int lane = threadIdx.x & 31, w = threadIdx.x >> 5, g = lane >> 2, t = lane & 3;
    if (threadIdx.x == 0) {
        mbar_init(smem_u32(&bar), 1);
        asm volatile("fence.mbarrier_init.release.cluster;" ::: "memory");
    }
    Trig16 tg(lane);
    uint32_t Are[2][4], Aim[2][4], Fc[4], Fs[4], Fn[4];
#pragma unroll
    for (int ks = 0; ks < 2; ks++)
#pragma unroll
        for (int r = 0; r < 4; r++) {
            int idx = (8 * ks + t + 4 * (r >> 1)) * perm_pi(g + 8 * (r & 1));
            float c = tg.C(idx), s = tg.Sn(idx);
            Are[ks][r] = pack_h2(c, -s); Aim[ks][r] = pack_h2(s, c);
        }
#pragma unroll
    for (int r = 0; r < 4; r++) {
        int e = g + 8 * (r & 1), k0 = 2 * t + 8 * (r >> 1);
        int i0 = e * k0, i1 = e * (k0 + 1);
        float c0 = tg.C(i0), c1 = tg.C(i1), s0 = tg.Sn(i0), s1 = tg.Sn(i1);
        Fc[r] = pack_h2(c0, c1); Fs[r] = pack_h2(s0, s1); Fn[r] = pack_h2(-s0, -s1);
    }
    float twc[2][4], tws[2][4];
#pragma unroll
    for (int jn = 0; jn < 2; jn++)
#pragma unroll
        for (int q = 0; q < 4; q++) {
            int c = 2 * g + (q >> 1), b = 2 * t + (q & 1) + 8 * jn;
            sincospif((float)(b * c) * (1.f / 128.f), &tws[jn][q], &twc[jn][q]);
        }
    __syncthreads();
    griddep_wait();
    griddep_launch();
    if (threadIdx.x == 0) {
        mbar_expect_tx(smem_u32(&bar), 16384);
        asm volatile("cp.async.bulk.shared::cluster.global.mbarrier::complete_tx::bytes [%0], [%1], %2, [%3];"
                     ::"r"(smem_u32(buf)), "l"(g_z2 + (size_t)blockIdx.x * 4096), "r"(16384), "r"(smem_u32(&bar)) : "memory");
    }
    const size_t row0 = (size_t)(blockIdx.x * 16 + 2 * w) * 512;
    uint4 xr[2][2];
#pragma unroll
    for (int k = 0; k < 2; k++)
#pragma unroll
        for (int h = 0; h < 2; h++) xr[k][h] = ((const uint4*)(x + row0 + k * 512))[4 * (g + 8 * h) + t];
    float winv;
    wscale_exp(lane, winv);
    mbar_wait(smem_u32(&bar), 0);
    const int f = ((g >> 1) & 1) | (t << 1);
    uint32_t B[2][4][2];
#pragma unroll
    for (int i = 0; i < 4; i++)
#pragma unroll
        for (int jn = 0; jn < 2; jn++) {
            int k = 16 * (t + 4 * i) + g + 8 * jn;
            uint2 q2 = *(const uint2*)&buf[k * 16 + 2 * (w ^ f)];
            B[0][i][jn] = q2.x; B[1][i][jn] = q2.y;
        }
    float v[2][16];
#pragma unroll
    for (int k = 0; k < 2; k++) {
        float Cre[2][4], Cim[2][4], Ore[2][4], Oim[2][4];
        stage_inter(Are, Aim, B[k], Cre, Cim);
#pragma unroll
        for (int jn = 0; jn < 2; jn++)
#pragma unroll
            for (int q = 0; q < 4; q++) {
                float re = Cre[jn][q], im = Cim[jn][q];
                Cre[jn][q] = re * twc[jn][q] - im * tws[jn][q];
                Cim[jn][q] = im * twc[jn][q] + re * tws[jn][q];
            }
        stage_c2b(Fc, Fn, Fs, Cre, Cim, Ore, Oim);
#pragma unroll
        for (int h = 0; h < 2; h++) {
            const uint32_t xw[4] = {xr[k][h].x, xr[k][h].y, xr[k][h].z, xr[k][h].w};
            uint32_t o[4];
#pragma unroll
            for (int i = 0; i < 4; i++) {
                float re = bf16r(Ore[i & 1][2 * h + (i >> 1)] * winv), im = bf16r(Oim[i & 1][2 * h + (i >> 1)] * winv);
                o[i] = pack_bf2(bf_lo(xw[i]) + re, bf_hi(xw[i]) + im);
                v[k][8 * h + 2 * i] = bf_lo(o[i]); v[k][8 * h + 2 * i + 1] = bf_hi(o[i]);
            }
            ((uint4*)(g_x1 + row0 + k * 512))[4 * (g + 8 * h) + t] = make_uint4(o[0], o[1], o[2], o[3]);
        }
    }
    warp_ln2(v);
    warp_ln2(v);
#pragma unroll
    for (int k = 0; k < 2; k++)
#pragma unroll
        for (int h = 0; h < 2; h++) {
            uint4 o;
            o.x = pack_bf2(v[k][8 * h + 0], v[k][8 * h + 1]); o.y = pack_bf2(v[k][8 * h + 2], v[k][8 * h + 3]);
            o.z = pack_bf2(v[k][8 * h + 4], v[k][8 * h + 5]); o.w = pack_bf2(v[k][8 * h + 6], v[k][8 * h + 7]);
            ((uint4*)(g_h + row0 + k * 512))[4 * (g + 8 * h) + t] = o;
        }
}

__device__ __forceinline__ uint64_t make_desc(uint32_t addr, uint32_t lbo, uint32_t sbo) {
    return (uint64_t)((addr & 0x3FFFF) >> 4) | ((uint64_t)((lbo & 0x3FFFF) >> 4) << 16) |
           ((uint64_t)((sbo & 0x3FFFF) >> 4) << 32) | ((uint64_t)1 << 62);
}
__device__ __forceinline__ void wgmma_m64n128(float (&d)[64], uint64_t da, uint64_t db) {
    asm volatile(
        "{\n.reg .pred p;\nsetp.ne.b32 p, 1, 0;\n"
        "wgmma.mma_async.sync.aligned.m64n128k16.f32.bf16.bf16 "
        "{%0,%1,%2,%3,%4,%5,%6,%7,%8,%9,%10,%11,%12,%13,%14,%15,"
        "%16,%17,%18,%19,%20,%21,%22,%23,%24,%25,%26,%27,%28,%29,%30,%31,"
        "%32,%33,%34,%35,%36,%37,%38,%39,%40,%41,%42,%43,%44,%45,%46,%47,"
        "%48,%49,%50,%51,%52,%53,%54,%55,%56,%57,%58,%59,%60,%61,%62,%63},"
        " %64, %65, p, 1, 1, 1, 1;\n}"
        : "+f"(d[0]), "+f"(d[1]), "+f"(d[2]), "+f"(d[3]), "+f"(d[4]), "+f"(d[5]), "+f"(d[6]), "+f"(d[7]),
          "+f"(d[8]), "+f"(d[9]), "+f"(d[10]), "+f"(d[11]), "+f"(d[12]), "+f"(d[13]), "+f"(d[14]), "+f"(d[15]),
          "+f"(d[16]), "+f"(d[17]), "+f"(d[18]), "+f"(d[19]), "+f"(d[20]), "+f"(d[21]), "+f"(d[22]), "+f"(d[23]),
          "+f"(d[24]), "+f"(d[25]), "+f"(d[26]), "+f"(d[27]), "+f"(d[28]), "+f"(d[29]), "+f"(d[30]), "+f"(d[31]),
          "+f"(d[32]), "+f"(d[33]), "+f"(d[34]), "+f"(d[35]), "+f"(d[36]), "+f"(d[37]), "+f"(d[38]), "+f"(d[39]),
          "+f"(d[40]), "+f"(d[41]), "+f"(d[42]), "+f"(d[43]), "+f"(d[44]), "+f"(d[45]), "+f"(d[46]), "+f"(d[47]),
          "+f"(d[48]), "+f"(d[49]), "+f"(d[50]), "+f"(d[51]), "+f"(d[52]), "+f"(d[53]), "+f"(d[54]), "+f"(d[55]),
          "+f"(d[56]), "+f"(d[57]), "+f"(d[58]), "+f"(d[59]), "+f"(d[60]), "+f"(d[61]), "+f"(d[62]), "+f"(d[63])
        : "l"(da), "l"(db));
}
__device__ __forceinline__ void tma_load_3d(uint32_t dst, const CUtensorMap* tm, int c0, int c1, int c2, uint32_t bar) {
    asm volatile(
        "cp.async.bulk.tensor.3d.shared::cluster.global.mbarrier::complete_tx::bytes [%0], [%1, {%3, %4, %5}], [%2];"
        ::"r"(dst), "l"(tm), "r"(bar), "r"(c0), "r"(c1), "r"(c2) : "memory");
}
__device__ __forceinline__ float gelu_tanh(float x) {
    const float k1 = -2.0f * 0.7978845608028654f * 1.4426950408889634f;
    const float k2 = k1 * 0.044715f;
    float z = x * fmaf(k2, x * x, k1);
    float e;
    asm("ex2.approx.ftz.f32 %0, %1;" : "=f"(e) : "f"(z));
    return __fdividef(x, 1.0f + e);
}

constexpr int G_BK = 64, G_STAGES = 8;
constexpr int G_A_BYTES = 64 * G_BK * 2, G_B_BYTES = 128 * G_BK * 2, G_STAGE_BYTES = G_A_BYTES + G_B_BYTES;
constexpr int G_SMEM = G_STAGES * G_STAGE_BYTES + 1024 + 256;

template <int EPI>
__global__ void __launch_bounds__(160) k_gemm(const __grid_constant__ CUtensorMap tmW, const __grid_constant__ CUtensorMap tmA,
                                              const bf16* __restrict__ bias, const bf16* __restrict__ resid,
                                              bf16* __restrict__ out, int nkb) {
    extern __shared__ uint8_t smem_raw[];
    const uint32_t base = (smem_u32(smem_raw) + 1023) & ~1023u;
    const uint32_t bars = base + G_STAGES * G_STAGE_BYTES;
    const int warp = threadIdx.x >> 5, lane = threadIdx.x & 31;
    const int mt = blockIdx.x >> 2, nt = blockIdx.x & 3;
    if (threadIdx.x == 0) {
        for (int i = 0; i < G_STAGES; i++) { mbar_init(bars + 8 * i, 1); mbar_init(bars + 8 * (G_STAGES + i), 4); }
        asm volatile("fence.mbarrier_init.release.cluster;" ::: "memory");
    }
    __syncthreads();
    if (warp == 4) {
        if (lane == 0) {
            for (int s = 0; s < G_STAGES; s++) {
                mbar_expect_tx(bars + 8 * s, G_STAGE_BYTES);
                tma_load_3d(base + s * G_STAGE_BYTES, &tmW, 0, s * G_BK, mt, bars + 8 * s);
            }
            griddep_wait();
            griddep_launch();
            for (int s = 0; s < G_STAGES; s++)
                tma_load_3d(base + s * G_STAGE_BYTES + G_A_BYTES, &tmA, 0, s * G_BK, nt * 2, bars + 8 * s);
            for (int kb = G_STAGES; kb < nkb; kb++) {
                int s = kb % G_STAGES;
                mbar_wait(bars + 8 * (G_STAGES + s), ((kb / G_STAGES) - 1) & 1);
                mbar_expect_tx(bars + 8 * s, G_STAGE_BYTES);
                tma_load_3d(base + s * G_STAGE_BYTES, &tmW, 0, kb * G_BK, mt, bars + 8 * s);
                tma_load_3d(base + s * G_STAGE_BYTES + G_A_BYTES, &tmA, 0, kb * G_BK, nt * 2, bars + 8 * s);
            }
        }
    } else {
        float acc[64];
#pragma unroll
        for (int i = 0; i < 64; i++) acc[i] = 0.f;
        for (int kb = 0; kb < nkb; kb++) {
            int s = kb % G_STAGES;
            mbar_wait(bars + 8 * s, (kb / G_STAGES) & 1);
            asm volatile("wgmma.fence.sync.aligned;" ::: "memory");
            uint32_t a0 = base + s * G_STAGE_BYTES, b0 = a0 + G_A_BYTES;
#pragma unroll
            for (int kk = 0; kk < G_BK / 16; kk++)
                wgmma_m64n128(acc, make_desc(a0 + kk * 2048, G_BK * 128, 1024), make_desc(b0 + kk * 2048, G_BK * 128, 1024));
            asm volatile("wgmma.commit_group.sync.aligned;" ::: "memory");
            asm volatile("wgmma.wait_group.sync.aligned 1;" ::: "memory");
            if (kb > 0 && lane == 0) mbar_arrive(bars + 8 * (G_STAGES + (kb - 1) % G_STAGES));
        }
        asm volatile("wgmma.wait_group.sync.aligned 0;" ::: "memory");
        griddep_wait();
        const int g = lane >> 2, t = lane & 3;
#pragma unroll
        for (int h = 0; h < 2; h++) {
            const int m = mt * 64 + warp * 16 + g + 8 * h;
            const float bv = __bfloat162float(bias[m]);
            const size_t off = (size_t)m * 512 + nt * 128 + 2 * t;
#pragma unroll
            for (int i = 0; i < 16; i++) {
                float v0 = bf16r(bf16r(acc[4 * i + 2 * h]) + bv), v1 = bf16r(bf16r(acc[4 * i + 2 * h + 1]) + bv);
                uint32_t o;
                if (EPI == 1) {
                    o = pack_bf2(gelu_tanh(v0), gelu_tanh(v1));
                } else {
                    uint32_t r = *(const uint32_t*)(resid + off + 8 * i);
                    o = pack_bf2(bf_lo(r) + v0, bf_hi(r) + v1);
                }
                *(uint32_t*)(out + off + 8 * i) = o;
            }
        }
    }
}

typedef CUresult (*EncodeFn)(CUtensorMap*, CUtensorMapDataType, cuuint32_t, void*, const cuuint64_t*, const cuuint64_t*,
                             const cuuint32_t*, const cuuint32_t*, CUtensorMapInterleave, CUtensorMapSwizzle,
                             CUtensorMapL2promotion, CUtensorMapFloatOOBfill);

void make_map(EncodeFn fn, CUtensorMap* tm, const void* ptr, int K, int M, int nchunk) {
    cuuint64_t dims[3] = {64, (cuuint64_t)K, (cuuint64_t)(M / 64)};
    cuuint64_t strides[2] = {(cuuint64_t)M * 2, 128};
    cuuint32_t box[3] = {64, (cuuint32_t)G_BK, (cuuint32_t)nchunk};
    cuuint32_t es[3] = {1, 1, 1};
    fn(tm, CU_TENSOR_MAP_DATA_TYPE_BFLOAT16, 3, (void*)ptr, dims, strides, box, es, CU_TENSOR_MAP_INTERLEAVE_NONE,
       CU_TENSOR_MAP_SWIZZLE_128B, CU_TENSOR_MAP_L2_PROMOTION_L2_256B, CU_TENSOR_MAP_FLOAT_OOB_FILL_NONE);
}

template <typename... KArgs, typename... Args>
void launch(void (*kern)(KArgs...), int grid, int block, int smem, bool pdl, Args... args) {
    cudaLaunchConfig_t cfg = {};
    cfg.gridDim = dim3(grid); cfg.blockDim = dim3(block); cfg.dynamicSmemBytes = smem; cfg.stream = cudaStreamPerThread;
    cudaLaunchAttribute at[1];
    at[0].id = cudaLaunchAttributeProgrammaticStreamSerialization;
    at[0].val.programmaticStreamSerializationAllowed = 1;
    cfg.attrs = at; cfg.numAttrs = pdl ? 1 : 0;
    cudaLaunchKernelEx(&cfg, kern, KArgs(args)...);
}

}

extern "C" void kernel_launch(void* const* d_in, const int* in_sizes, int n_in, void* d_out, int out_size) {
    const bf16* x = (const bf16*)d_in[0];
    const bf16* wr = (const bf16*)d_in[1];
    const bf16* wi = (const bf16*)d_in[2];
    const bf16* w1 = (const bf16*)d_in[4];
    const bf16* b1 = (const bf16*)d_in[5];
    const bf16* w2 = (const bf16*)d_in[6];
    const bf16* b2 = (const bf16*)d_in[7];
    bf16* out = (bf16*)d_out;

    static EncodeFn enc = nullptr;
    static bf16 *p_x1, *p_h, *p_u, *p_x2;
    if (!enc) {
        cudaDriverEntryPointQueryResult qr;
        void* fn = nullptr;
        cudaGetDriverEntryPoint("cuTensorMapEncodeTiled", &fn, cudaEnableDefault, &qr);
        enc = (EncodeFn)fn;
        cudaGetSymbolAddress((void**)&p_x1, g_x1);
        cudaGetSymbolAddress((void**)&p_h, g_h);
        cudaGetSymbolAddress((void**)&p_u, g_u);
        cudaGetSymbolAddress((void**)&p_x2, g_x2);
        cudaFuncSetAttribute(k_gemm<1>, cudaFuncAttributeMaxDynamicSharedMemorySize, G_SMEM);
        cudaFuncSetAttribute(k_gemm<2>, cudaFuncAttributeMaxDynamicSharedMemorySize, G_SMEM);
    }
    CUtensorMap tmW1, tmW2, tmH, tmU;
    make_map(enc, &tmW1, w1, S_, F_, 1);
    make_map(enc, &tmW2, w2, F_, S_, 1);
    make_map(enc, &tmH, p_h, S_, D_, 2);
    make_map(enc, &tmU, p_u, F_, D_, 2);

    for (int layer = 0; layer < 2; layer++) {
        const bf16* xin = layer == 0 ? x : p_x2;
        bf16* xout = layer == 0 ? p_x2 : out;
        launch(k_p1, layer == 0 ? 192 : 128, 256, 0, layer != 0, xin, wr, wi);
        launch(k_p2, 129, 256, 0, true);
        launch(k_p3, 128, 256, 0, true, xin);
        launch(k_gemm<1>, (F_ / 64) * 4, 160, G_SMEM, true, tmW1, tmH, b1, (const bf16*)nullptr, p_u, S_ / G_BK);
        launch(k_gemm<2>, (S_ / 64) * 4, 160, G_SMEM, true, tmW2, tmU, b2, (const bf16*)p_x1, xout, F_ / G_BK);
    }
}
```

```cpp
#include <cuda_runtime.h>
#include <cuda_bf16.h>
#include <cuda_fp16.h>
#include <cuda.h>
#include <stdint.h>

typedef __nv_bfloat16 bf16;

namespace {

constexpr int S_ = 2048, D_ = 512, F_ = 1792;

__device__ const __align__(16) uint32_t TAB_P1[1408] = {
0x3400,0x3400,0x3400,0x3400,0x3400,0xb400,0x3400,0xb400,0x3400,0x3400,0x3400,0x3400,
0x3400,0xb400,0x3400,0xb400,0x3400,0x3400,0x3400,0x3400,0x34000000,0xb4000000,0x34000000,0xb4000000,
0xb400,0xb400,0xb400,0xb400,0xb4000000,0x34000000,0xb4000000,0x34000000,0x3400,0x3400,0x34000000,0x34000000,
0x2e1f3364,0xae1fb364,0x3364ae1f,0xb3642e1f,0x31a831a8,0x31a831a8,0x31a8b1a8,0x31a8b1a8,0x33642e1f,0xb364ae1f,0x2e1fb364,0xae1f3364,
0x3400,0x3400,0x34000000,0x34000000,0x3364ae1f,0xb3642e1f,0xae1fb364,0x2e1f3364,0xb1a8b1a8,0xb1a8b1a8,0xb1a831a8,0xb1a831a8,
0xae1f3364,0x2e1fb364,0x33642e1f,0xb364ae1f,0x3400,0x3400,0xb400,0xb400,0x31a831a8,0xb1a8b1a8,0xb1a8b1a8,0x31a831a8,
0x34000000,0x34000000,0xb4000000,0xb4000000,0x31a8b1a8,0xb1a831a8,0xb1a831a8,0x31a8b1a8,0x3400,0x3400,0xb400,0xb400,
0x31a8b1a8,0xb1a831a8,0xb1a831a8,0x31a8b1a8,0xb4000000,0xb4000000,0x34000000,0x34000000,0x31a831a8,0xb1a8b1a8,0xb1a8b1a8,0x31a831a8,
0x3400,0x3400,0xb4000000,0xb4000000,0x33642e1f,0xb364ae1f,0xae1f3364,0x2e1fb364,0x31a8b1a8,0x31a8b1a8,0x31a831a8,0x31a831a8,
0xae1fb364,0x2e1f3364,0x3364ae1f,0xb3642e1f,0x3400,0x3400,0xb4000000,0xb4000000,0x2e1fb364,0xae1f3364,0x33642e1f,0xb364ae1f,
0xb1a831a8,0xb1a831a8,0xb1a8b1a8,0xb1a8b1a8,0x3364ae1f,0xb3642e1f,0x2e1f3364,0xae1fb364,0x3400,0x3400,0x3400,0x3400,
0x3400,0xb400,0x3400,0xb400,0x3400,0x3400,0x3400,0x3400,0x3400,0xb400,0x3400,0xb400,
0x3400,0x3400,0x3400,0x3400,0x34000000,0xb4000000,0x34000000,0xb4000000,0xb400,0xb400,0xb400,0xb400,
0xb4000000,0x34000000,0xb4000000,0x34000000,0xb400,0xb400,0xb4000000,0xb4000000,0xae1fb364,0x2e1f3364,0xb3642e1f,0x3364ae1f,
0xb1a8b1a8,0xb1a8b1a8,0xb1a831a8,0xb1a831a8,0xb364ae1f,0x33642e1f,0xae1f3364,0x2e1fb364,0xb400,0xb400,0xb4000000,0xb4000000,
0xb3642e1f,0x3364ae1f,0x2e1f3364,0xae1fb364,0x31a831a8,0x31a831a8,0x31a8b1a8,0x31a8b1a8,0x2e1fb364,0xae1f3364,0xb364ae1f,0x33642e1f,
0x3400,0x3400,0xb400,0xb400,0x31a831a8,0xb1a8b1a8,0xb1a8b1a8,0x31a831a8,0x34000000,0x34000000,0xb4000000,0xb4000000,
0x31a8b1a8,0xb1a831a8,0xb1a831a8,0x31a8b1a8,0x3400,0x3400,0xb400,0xb400,0x31a8b1a8,0xb1a831a8,0xb1a831a8,0x31a8b1a8,
0xb4000000,0xb4000000,0x34000000,0x34000000,0x31a831a8,0xb1a8b1a8,0xb1a8b1a8,0x31a831a8,0xb400,0xb400,0x34000000,0x34000000,
0xb364ae1f,0x33642e1f,0x2e1fb364,0xae1f3364,0xb1a831a8,0xb1a831a8,0xb1a8b1a8,0xb1a8b1a8,0x2e1f3364,0xae1fb364,0xb3642e1f,0x3364ae1f,
0xb400,0xb400,0x34000000,0x34000000,0xae1f3364,0x2e1fb364,0xb364ae1f,0x33642e1f,0x31a8b1a8,0x31a8b1a8,0x31a831a8,0x31a831a8,
0xb3642e1f,0x3364ae1f,0xae1fb364,0x2e1f3364,0x34008000,0x34008000,0x34008000,0x34008000,0x34008000,0xb4008000,0x34008000,0xb4008000,
0x34008000,0x34008000,0x34008000,0x34008000,0x34008000,0xb4008000,0x34008000,0xb4008000,0x34008000,0x34008000,0x34008000,0x34008000,
0xb400,0x3400,0xb400,0x3400,0xb4008000,0xb4008000,0xb4008000,0xb4008000,0x3400,0xb400,0x3400,0xb400,
0x34008000,0x34008000,0xb400,0xb400,0x3364ae1f,0xb3642e1f,0xae1fb364,0x2e1f3364,0x31a8b1a8,0x31a8b1a8,0xb1a8b1a8,0xb1a8b1a8,
0x2e1fb364,0xae1f3364,0xb364ae1f,0x33642e1f,0x34008000,0x34008000,0xb400,0xb400,0xae1fb364,0x2e1f3364,0xb3642e1f,0x3364ae1f,
0xb1a831a8,0xb1a831a8,0x31a831a8,0x31a831a8,0x33642e1f,0xb364ae1f,0x2e1fb364,0xae1f3364,0x34008000,0x34008000,0xb4008000,0xb4008000,
0x31a8b1a8,0xb1a831a8,0xb1a831a8,0x31a8b1a8,0xb400,0xb400,0x3400,0x3400,0xb1a8b1a8,0x31a831a8,0x31a831a8,0xb1a8b1a8,
0x34008000,0x34008000,0xb4008000,0xb4008000,0xb1a8b1a8,0x31a831a8,0x31a831a8,0xb1a8b1a8,0x3400,0x3400,0xb400,0xb400,
0x31a8b1a8,0xb1a831a8,0xb1a831a8,0x31a8b1a8,0x34008000,0x34008000,0x3400,0x3400,0x2e1fb364,0xae1f3364,0x33642e1f,0xb364ae1f,
0xb1a8b1a8,0xb1a8b1a8,0x31a8b1a8,0x31a8b1a8,0xb3642e1f,0x3364ae1f,0xae1fb364,0x2e1f3364,0x34008000,0x34008000,0x3400,0x3400,
0xb364ae1f,0x33642e1f,0x2e1fb364,0xae1f3364,0x31a831a8,0x31a831a8,0xb1a831a8,0xb1a831a8,0xae1fb364,0x2e1f3364,0x3364ae1f,0xb3642e1f,
0x34008000,0x34008000,0x34008000,0x34008000,0x34008000,0xb4008000,0x34008000,0xb4008000,0x34008000,0x34008000,0x34008000,0x34008000,
0x34008000,0xb4008000,0x34008000,0xb4008000,0x34008000,0x34008000,0x34008000,0x34008000,0xb400,0x3400,0xb400,0x3400,
0xb4008000,0xb4008000,0xb4008000,0xb4008000,0x3400,0xb400,0x3400,0xb400,0xb4008000,0xb4008000,0x3400,0x3400,
0xb3642e1f,0x3364ae1f,0x2e1f3364,0xae1fb364,0xb1a831a8,0xb1a831a8,0x31a831a8,0x31a831a8,0xae1f3364,0x2e1fb364,0x33642e1f,0xb364ae1f,
0xb4008000,0xb4008000,0x3400,0x3400,0x2e1f3364,0xae1fb364,0x3364ae1f,0xb3642e1f,0x31a8b1a8,0x31a8b1a8,0xb1a8b1a8,0xb1a8b1a8,
0xb364ae1f,0x33642e1f,0xae1f3364,0x2e1fb364,0x34008000,0x34008000,0xb4008000,0xb4008000,0x31a8b1a8,0xb1a831a8,0xb1a831a8,0x31a8b1a8,
0xb400,0xb400,0x3400,0x3400,0xb1a8b1a8,0x31a831a8,0x31a831a8,0xb1a8b1a8,0x34008000,0x34008000,0xb4008000,0xb4008000,
0xb1a8b1a8,0x31a831a8,0x31a831a8,0xb1a8b1a8,0x3400,0x3400,0xb400,0xb400,0x31a8b1a8,0xb1a831a8,0xb1a831a8,0x31a8b1a8,
0xb4008000,0xb4008000,0xb400,0xb400,0xae1f3364,0x2e1fb364,0xb364ae1f,0x33642e1f,0x31a831a8,0x31a831a8,0xb1a831a8,0xb1a831a8,
0x3364ae1f,0xb3642e1f,0x2e1f3364,0xae1fb364,0xb4008000,0xb4008000,0xb400,0xb400,0x33642e1f,0xb364ae1f,0xae1f3364,0x2e1fb364,
0xb1a8b1a8,0xb1a8b1a8,0x31a8b1a8,0x31a8b1a8,0x2e1f3364,0xae1fb364,0xb3642e1f,0x3364ae1f,0x34003400,0x34003400,0x34003400,0xb400b400,
0x34003400,0x34003400,0x34003400,0xb400b400,0x34003400,0x34003400,0x34003400,0xb400b400,0x34003400,0x34003400,0x34003400,0xb400b400,
0x31a83400,0x31a83400,0x2e1f3364,0xae1fb364,0xb1a80000,0xb1a80000,0xb364ae1f,0x33642e1f,0xb1a8b400,0xb1a8b400,0xae1fb364,0x2e1f3364,
0x31a80000,0x31a80000,0x33642e1f,0xb364ae1f,0x3400,0x3400,0xb1a831a8,0x31a8b1a8,0xb400,0xb400,0x31a8b1a8,0xb1a831a8,
0x3400,0x3400,0xb1a831a8,0x31a8b1a8,0xb400,0xb400,0x31a8b1a8,0xb1a831a8,0xb1a83400,0xb1a83400,0xb3642e1f,0x3364ae1f,
0x31a80000,0x31a80000,0xae1f3364,0x2e1fb364,0x31a8b400,0x31a8b400,0x3364ae1f,0xb3642e1f,0xb1a80000,0xb1a80000,0x2e1fb364,0xae1f3364,
0xb4003400,0xb4003400,0x0,0x0,0xb4003400,0xb4003400,0x0,0x0,0xb4003400,0xb4003400,0x0,0x0,
0xb4003400,0xb4003400,0x0,0x0,0xb1a83400,0xb1a83400,0x3364ae1f,0xb3642e1f,0x31a80000,0x31a80000,0x2e1fb364,0xae1f3364,
0x31a8b400,0x31a8b400,0xb3642e1f,0x3364ae1f,0xb1a80000,0xb1a80000,0xae1f3364,0x2e1fb364,0x3400,0x3400,0x31a8b1a8,0xb1a831a8,
0xb400,0xb400,0xb1a831a8,0x31a8b1a8,0x3400,0x3400,0x31a8b1a8,0xb1a831a8,0xb400,0xb400,0xb1a831a8,0x31a8b1a8,
0x31a83400,0x31a83400,0xae1fb364,0x2e1f3364,0xb1a80000,0xb1a80000,0x33642e1f,0xb364ae1f,0xb1a8b400,0xb1a8b400,0x2e1f3364,0xae1fb364,
0x31a80000,0x31a80000,0xb364ae1f,0x33642e1f,0x0,0x0,0x0,0x0,0x0,0x0,0x0,0x0,
0x0,0x0,0x0,0x0,0x0,0x0,0x0,0x0,0x31a80000,0x31a80000,0x33642e1f,0xb364ae1f,
0x31a83400,0x31a83400,0x2e1f3364,0xae1fb364,0xb1a80000,0xb1a80000,0xb364ae1f,0x33642e1f,0xb1a8b400,0xb1a8b400,0xae1fb364,0x2e1f3364,
0x34000000,0x34000000,0x31a831a8,0xb1a8b1a8,0xb4000000,0xb4000000,0xb1a8b1a8,0x31a831a8,0x34000000,0x34000000,0x31a831a8,0xb1a8b1a8,
0xb4000000,0xb4000000,0xb1a8b1a8,0x31a831a8,0x31a80000,0x31a80000,0xae1f3364,0x2e1fb364,0x31a8b400,0x31a8b400,0x3364ae1f,0xb3642e1f,
0xb1a80000,0xb1a80000,0x2e1fb364,0xae1f3364,0xb1a83400,0xb1a83400,0xb3642e1f,0x3364ae1f,0x0,0x0,0xb4003400,0x3400b400,
0x0,0x0,0xb4003400,0x3400b400,0x0,0x0,0xb4003400,0x3400b400,0x0,0x0,0xb4003400,0x3400b400,
0xb1a80000,0xb1a80000,0xae1f3364,0x2e1fb364,0xb1a83400,0xb1a83400,0x3364ae1f,0xb3642e1f,0x31a80000,0x31a80000,0x2e1fb364,0xae1f3364,
0x31a8b400,0x31a8b400,0xb3642e1f,0x3364ae1f,0xb4000000,0xb4000000,0x31a831a8,0xb1a8b1a8,0x34000000,0x34000000,0xb1a8b1a8,0x31a831a8,
0xb4000000,0xb4000000,0x31a831a8,0xb1a8b1a8,0x34000000,0x34000000,0xb1a8b1a8,0x31a831a8,0xb1a80000,0xb1a80000,0x33642e1f,0xb364ae1f,
0xb1a8b400,0xb1a8b400,0x2e1f3364,0xae1fb364,0x31a80000,0x31a80000,0xb364ae1f,0x33642e1f,0x31a83400,0x31a83400,0xae1fb364,0x2e1f3364,
0x80008000,0x80008000,0x80008000,0x80008000,0x80008000,0x80008000,0x80008000,0x80008000,0x80008000,0x80008000,0x80008000,0x80008000,
0x80008000,0x80008000,0x80008000,0x80008000,0xb1a88000,0xb1a88000,0xb364ae1f,0x33642e1f,0xb1a8b400,0xb1a8b400,0xae1fb364,0x2e1f3364,
0x31a88000,0x31a88000,0x33642e1f,0xb364ae1f,0x31a83400,0x31a83400,0x2e1f3364,0xae1fb364,0xb4008000,0xb4008000,0xb1a8b1a8,0x31a831a8,
0x34008000,0x34008000,0x31a831a8,0xb1a8b1a8,0xb4008000,0xb4008000,0xb1a8b1a8,0x31a831a8,0x34008000,0x34008000,0x31a831a8,0xb1a8b1a8,
0xb1a88000,0xb1a88000,0x2e1fb364,0xae1f3364,0xb1a83400,0xb1a83400,0xb3642e1f,0x3364ae1f,0x31a88000,0x31a88000,0xae1f3364,0x2e1fb364,
0x31a8b400,0x31a8b400,0x3364ae1f,0xb3642e1f,0x80008000,0x80008000,0x3400b400,0xb4003400,0x80008000,0x80008000,0x3400b400,0xb4003400,
0x80008000,0x80008000,0x3400b400,0xb4003400,0x80008000,0x80008000,0x3400b400,0xb4003400,0x31a88000,0x31a88000,0x2e1fb364,0xae1f3364,
0x31a8b400,0x31a8b400,0xb3642e1f,0x3364ae1f,0xb1a88000,0xb1a88000,0xae1f3364,0x2e1fb364,0xb1a83400,0xb1a83400,0x3364ae1f,0xb3642e1f,
0x34008000,0x34008000,0xb1a8b1a8,0x31a831a8,0xb4008000,0xb4008000,0x31a831a8,0xb1a8b1a8,0x34008000,0x34008000,0xb1a8b1a8,0x31a831a8,
0xb4008000,0xb4008000,0x31a831a8,0xb1a8b1a8,0x31a88000,0x31a88000,0xb364ae1f,0x33642e1f,0x31a83400,0x31a83400,0xae1fb364,0x2e1f3364,
0xb1a88000,0xb1a88000,0x33642e1f,0xb364ae1f,0xb1a8b400,0xb1a8b400,0x2e1f3364,0xae1fb364,0x3f800000,0x3f800000,0x3f800000,0x3f6c835e,
0x3f800000,0x3f800000,0x3f3504f3,0x3ec3ef15,0x3f800000,0x3f800000,0x0,0xbec3ef15,0x3f800000,0x3f800000,0xbf3504f3,0xbf6c835e,
0x3f800000,0x3f7b14be,0x3f800000,0x3f54db31,0x3f6c835e,0x3f54db31,0x3ec3ef15,0xbe47c5c2,0x3f3504f3,0x3f0e39da,0xbf3504f3,0xbf7b14be,
0x3ec3ef15,0x3e47c5c2,0xbf6c835e,0xbf0e39da,0x3f800000,0x3f7fb10f,0x3f800000,0x3f676bd8,0x3f7ec46d,0x3f7d3aac,0x3f226799,0x3e78cfcc,
0x3f7b14be,0x3f7853f8,0xbe47c5c2,0xbf187fc0,0x3f74fa0b,0x3f710908,0xbf61c598,0xbf7fb10f,0x3f800000,0x3f7853f8,0x3f800000,0x3f4d9f02,
0x3f61c598,0x3f3daef9,0x3e94a031,0xbeac7cd4,0x3f0e39da,0x3eac7cd4,0xbf54db31,0xbf7fb10f,0x3dc8bd36,0xbe164083,0xbf45e403,0xbe78cfcc,
0x3f800000,0x3f7ec46d,0x3f800000,0x3f61c598,0x3f7b14be,0x3f74fa0b,0x3f0e39da,0x3dc8bd36,0x3f6c835e,0x3f61c598,0xbec3ef15,0xbf45e403,
0x3f54db31,0x3f45e403,0xbf7b14be,0xbf74fa0b,0x3f800000,0x3f74fa0b,0x3f800000,0x3f45e403,0x3f54db31,0x3f226799,0x3e47c5c2,0xbef15aea,
0x3ec3ef15,0x3dc8bd36,0xbf6c835e,0xbf74fa0b,0xbe47c5c2,0xbef15aea,0xbf0e39da,0x3dc8bd36,0x3f800000,0x3f7d3aac,0x3f800000,0x3f5b941a,
0x3f74fa0b,0x3f676bd8,0x3ef15aea,0xbd48fb30,0x3f54db31,0x3f3daef9,0xbf0e39da,0xbf676bd8,0x3f226799,0x3f039c3d,0xbf7ec46d,0xbf4d9f02,
0x3f800000,0x3f710908,0x3f800000,0x3f3daef9,0x3f45e403,0x3f039c3d,0x3dc8bd36,0xbf187fc0,0x3e47c5c2,0xbe164083,0xbf7b14be,0xbf5b941a,
0xbef15aea,0xbf3daef9,0xbe94a031,0x3edae880,0x3f800000,0x3f800000,0x3f7b14be,0x3f54db31,0x3f800000,0x3f800000,0x3f0e39da,0x3e47c5c2,
0x3f800000,0x3f800000,0xbe47c5c2,0xbf0e39da,0x3f800000,0x3f800000,0xbf54db31,0xbf7b14be,0x3f7ec46d,0x3f74fa0b,0x3f74fa0b,0x3f226799,
0x3f61c598,0x3f45e403,0x3dc8bd36,0xbef15aea,0x3f226799,0x3ef15aea,0xbf61c598,0xbf7ec46d,0x3e94a031,0x3dc8bd36,0xbf45e403,0xbe94a031,
0x3f7fec43,0x3f7f4e6d,0x3f79c79d,0x3f49d112,0x3f7e1324,0x3f7c3b28,0x3ee63375,0x3cc90ab0,0x3f79c79d,0x3f76ba07,0xbecf7bca,0xbf41d870,
0x3f731447,0x3f6ed89e,0xbf76ba07,0xbf7c3b28,0x3f7e1324,0x3f6ed89e,0x3f731447,0x3f13682a,0x3f514d3d,0x3f273656,0xbcc90ab0,0xbf1d7fd1,
0x3ee63375,0x3e605c13,0xbf76ba07,0xbf6ed89e,0xbcc90ab0,0xbe888e93,0xbf08f59b,0x3d96a905,0x3f7fb10f,0x3f7d3aac,0x3f7853f8,0x3f3daef9,
0x3f7853f8,0x3f710908,0x3eac7cd4,0xbe164083,0x3f676bd8,0x3f5b941a,0xbf187fc0,0xbf676bd8,0x3f4d9f02,0x3f3daef9,0xbf7fb10f,0xbf5b941a,
0x3f7d3aac,0x3f676bd8,0x3f710908,0x3f039c3d,0x3f3daef9,0x3f039c3d,0xbe164083,0xbf3daef9,0x3e78cfcc,0xbd48fb30,0xbf7fb10f,0xbf4d9f02,
0xbeac7cd4,0xbf187fc0,0xbe78cfcc,0x3edae880,0x3f7f4e6d,0x3f79c79d,0x3f76ba07,0x3f3085bb,0x3f6ed89e,0x3f5ebe05,0x3e605c13,0xbea09ae5,
0x3f49d112,0x3f3085bb,0xbf41d870,0xbf7c3b28,0x3f13682a,0x3ee63375,0xbf6ed89e,0xbf1d7fd1,0x3f7c3b28,0x3f5ebe05,0x3f6ed89e,0x3ee63375,
0x3f273656,0x3eb8442a,0xbe888e93,0xbf584853,0x3cc90ab0,0xbea09ae5,0xbf7c3b28,0xbf1d7fd1,0xbf1d7fd1,0xbf584853,0x3d96a905,0x3f396842,
0x0,0x0,0x0,0x3ec3ef15,0x0,0x0,0x3f3504f3,0x3f6c835e,0x0,0x0,0x3f800000,0x3f6c835e,
0x0,0x0,0x3f3504f3,0x3ec3ef15,0x0,0x3e47c5c2,0x0,0x3f0e39da,0x3ec3ef15,0x3f0e39da,0x3f6c835e,0x3f7b14be,
0x3f3504f3,0x3f54db31,0x3f3504f3,0x3e47c5c2,0x3f6c835e,0x3f7b14be,0xbec3ef15,0xbf54db31,0x0,0x3d48fb30,0x0,0x3edae880,
0x3dc8bd36,0x3e164083,0x3f45e403,0x3f7853f8,0x3e47c5c2,0x3e78cfcc,0x3f7b14be,0x3f4d9f02,0x3e94a031,0x3eac7cd4,0x3ef15aea,0x3d48fb30,
0x0,0x3e78cfcc,0x0,0x3f187fc0,0x3ef15aea,0x3f2beb4a,0x3f74fa0b,0x3f710908,0x3f54db31,0x3f710908,0x3f0e39da,0xbd48fb30,
0x3f7ec46d,0x3f7d3aac,0xbf226799,0xbf7853f8,0x0,0x3dc8bd36,0x0,0x3ef15aea,0x3e47c5c2,0x3e94a031,0x3f54db31,0x3f7ec46d,
0x3ec3ef15,0x3ef15aea,0x3f6c835e,0x3f226799,0x3f0e39da,0x3f226799,0x3e47c5c2,0xbe94a031,0x0,0x3e94a031,0x0,0x3f226799,
0x3f0e39da,0x3f45e403,0x3f7b14be,0x3f61c598,0x3f6c835e,0x3f7ec46d,0x3ec3ef15,0xbe94a031,0x3f7b14be,0x3f61c598,0xbf54db31,0xbf7ec46d,
0x0,0x3e164083,0x0,0x3f039c3d,0x3e94a031,0x3edae880,0x3f61c598,0x3f7fb10f,0x3f0e39da,0x3f2beb4a,0x3f54db31,0x3edae880,
0x3f45e403,0x3f5b941a,0xbdc8bd36,0xbf187fc0,0x0,0x3eac7cd4,0x0,0x3f2beb4a,0x3f226799,0x3f5b941a,0x3f7ec46d,0x3f4d9f02,
0x3f7b14be,0x3f7d3aac,0x3e47c5c2,0xbf039c3d,0x3f61c598,0x3f2beb4a,0xbf74fa0b,0xbf676bd8,0x0,0x0,0x3e47c5c2,0x3f0e39da,
0x0,0x0,0x3f54db31,0x3f7b14be,0x0,0x0,0x3f7b14be,0x3f54db31,0x0,0x0,0x3f0e39da,0x3e47c5c2,
0x3dc8bd36,0x3e94a031,0x3e94a031,0x3f45e403,0x3ef15aea,0x3f226799,0x3f7ec46d,0x3f61c598,0x3f45e403,0x3f61c598,0x3ef15aea,0xbdc8bd36,
0x3f74fa0b,0x3f7ec46d,0xbf226799,0xbf74fa0b,0x3cc90ab0,0x3d96a905,0x3e605c13,0x3f1d7fd1,0x3dfab273,0x3e2f10a2,0x3f64aa59,0x3f7fec43,
0x3e605c13,0x3e888e93,0x3f6a09a7,0x3f273656,0x3ea09ae5,0x3eb8442a,0x3e888e93,0xbe2f10a2,0x3dfab273,0x3eb8442a,0x3ea09ae5,0x3f514d3d,
0x3f13682a,0x3f41d870,0x3f7fec43,0x3f49d112,0x3f64aa59,0x3f79c79d,0x3e888e93,0xbeb8442a,0x3f7fec43,0x3f76ba07,0xbf584853,0xbf7f4e6d,
0x3d48fb30,0x3e164083,0x3e78cfcc,0x3f2beb4a,0x3e78cfcc,0x3eac7cd4,0x3f710908,0x3f7d3aac,0x3edae880,0x3f039c3d,0x3f4d9f02,0x3edae880,
0x3f187fc0,0x3f2beb4a,0xbd48fb30,0xbf039c3d,0x3e164083,0x3edae880,0x3eac7cd4,0x3f5b941a,0x3f2beb4a,0x3f5b941a,0x3f7d3aac,0x3f2beb4a,
0x3f7853f8,0x3f7fb10f,0x3d48fb30,0xbf187fc0,0x3f710908,0x3f4d9f02,0xbf7853f8,0xbf676bd8,0x3d96a905,0x3e605c13,0x3e888e93,0x3f396842,
0x3eb8442a,0x3efc5d27,0x3f79c79d,0x3f731447,0x3f1d7fd1,0x3f396842,0x3f273656,0x3e2f10a2,0x3f514d3d,0x3f64aa59,0xbeb8442a,0xbf49d112,
0x3e2f10a2,0x3efc5d27,0x3eb8442a,0x3f64aa59,0x3f41d870,0x3f6ed89e,0x3f76ba07,0x3f08f59b,0x3f7fec43,0x3f731447,0xbe2f10a2,0xbf49d112,
0x3f49d112,0x3f08f59b,0xbf7f4e6d,0xbf3085bb,
};
__device__ const __align__(16) uint32_t TAB_P2[1920] = {
0x3400,0x3400,0x3400,0x34000000,0x3400,0x2e1f3364,0x3400,0x3364ae1f,0x3400,0x31a831a8,0x3400,0x31a8b1a8,
0x3400,0x33642e1f,0x3400,0x2e1fb364,0x3400,0x3400,0xb400,0xb4000000,0x31a831a8,0x33642e1f,0xb1a8b1a8,0xae1f3364,
0x34000000,0x31a8b1a8,0xb4000000,0x31a831a8,0x31a8b1a8,0xae1fb364,0xb1a831a8,0x3364ae1f,0x3400,0x3400,0x3400,0x34000000,
0x34000000,0x3364ae1f,0x34000000,0xae1fb364,0xb400,0xb1a8b1a8,0xb400,0xb1a831a8,0xb4000000,0xae1f3364,0xb4000000,0x33642e1f,
0x3400,0x3400,0xb400,0xb4000000,0x31a8b1a8,0x2e1fb364,0xb1a831a8,0x33642e1f,0xb4000000,0xb1a831a8,0x34000000,0xb1a8b1a8,
0x31a831a8,0x3364ae1f,0xb1a8b1a8,0x2e1f3364,0x3400,0x3400,0x3400,0x34000000,0xb400,0xae1fb364,0xb400,0xb3642e1f,
0x3400,0x31a831a8,0x3400,0x31a8b1a8,0xb400,0xb364ae1f,0xb400,0xae1f3364,0x3400,0x3400,0xb400,0xb4000000,
0xb1a8b1a8,0xb364ae1f,0x31a831a8,0x2e1fb364,0x34000000,0x31a8b1a8,0xb4000000,0x31a831a8,0xb1a831a8,0x2e1f3364,0x31a8b1a8,0xb3642e1f,
0x3400,0x3400,0x3400,0x34000000,0xb4000000,0xb3642e1f,0xb4000000,0x2e1f3364,0xb400,0xb1a8b1a8,0xb400,0xb1a831a8,
0x34000000,0x2e1fb364,0x34000000,0xb364ae1f,0x3400,0x3400,0xb400,0xb4000000,0xb1a831a8,0xae1f3364,0x31a8b1a8,0xb364ae1f,
0xb4000000,0xb1a831a8,0x34000000,0xb1a8b1a8,0xb1a8b1a8,0xb3642e1f,0x31a831a8,0xae1fb364,0x3400,0xb400,0x3400,0xb4000000,
0x3400,0xae1fb364,0x3400,0xb3642e1f,0x3400,0xb1a8b1a8,0x3400,0xb1a831a8,0x3400,0xb364ae1f,0x3400,0xae1f3364,
0x3400,0xb400,0xb400,0x34000000,0x31a831a8,0xb364ae1f,0xb1a8b1a8,0x2e1fb364,0x34000000,0xb1a831a8,0xb4000000,0xb1a8b1a8,
0x31a8b1a8,0x2e1f3364,0xb1a831a8,0xb3642e1f,0x3400,0xb400,0x3400,0xb4000000,0x34000000,0xb3642e1f,0x34000000,0x2e1f3364,
0xb400,0x31a831a8,0xb400,0x31a8b1a8,0xb4000000,0x2e1fb364,0xb4000000,0xb364ae1f,0x3400,0xb400,0xb400,0x34000000,
0x31a8b1a8,0xae1f3364,0xb1a831a8,0xb364ae1f,0xb4000000,0x31a8b1a8,0x34000000,0x31a831a8,0x31a831a8,0xb3642e1f,0xb1a8b1a8,0xae1fb364,
0x3400,0xb400,0x3400,0xb4000000,0xb400,0x2e1f3364,0xb400,0x3364ae1f,0x3400,0xb1a8b1a8,0x3400,0xb1a831a8,
0xb400,0x33642e1f,0xb400,0x2e1fb364,0x3400,0xb400,0xb400,0x34000000,0xb1a8b1a8,0x33642e1f,0x31a831a8,0xae1f3364,
0x34000000,0xb1a831a8,0xb4000000,0xb1a8b1a8,0xb1a831a8,0xae1fb364,0x31a8b1a8,0x3364ae1f,0x3400,0xb400,0x3400,0xb4000000,
0xb4000000,0x3364ae1f,0xb4000000,0xae1fb364,0xb400,0x31a831a8,0xb400,0x31a8b1a8,0x34000000,0xae1f3364,0x34000000,0x33642e1f,
0x3400,0xb400,0xb400,0x34000000,0xb1a831a8,0x2e1fb364,0x31a8b1a8,0x33642e1f,0xb4000000,0x31a8b1a8,0x34000000,0x31a831a8,
0xb1a8b1a8,0x3364ae1f,0x31a831a8,0x2e1f3364,0x34008000,0x34008000,0x34008000,0xb400,0x34008000,0x3364ae1f,0x34008000,0xae1fb364,
0x34008000,0x31a8b1a8,0x34008000,0xb1a8b1a8,0x34008000,0x2e1fb364,0x34008000,0xb364ae1f,0x34008000,0x34008000,0xb4008000,0x3400,
0x31a8b1a8,0x2e1fb364,0xb1a831a8,0x33642e1f,0xb400,0xb1a8b1a8,0x3400,0x31a8b1a8,0xb1a8b1a8,0xb3642e1f,0x31a831a8,0xae1fb364,
0x34008000,0x34008000,0x34008000,0xb400,0xb400,0xae1fb364,0xb400,0xb3642e1f,0xb4008000,0xb1a831a8,0xb4008000,0x31a831a8,
0x3400,0x33642e1f,0x3400,0x2e1fb364,0x34008000,0x34008000,0xb4008000,0x3400,0xb1a8b1a8,0xb364ae1f,0x31a831a8,0x2e1fb364,
0x3400,0x31a831a8,0xb400,0xb1a831a8,0x31a8b1a8,0xae1fb364,0xb1a831a8,0x3364ae1f,0x34008000,0x34008000,0x34008000,0xb400,
0xb4008000,0xb3642e1f,0xb4008000,0x2e1f3364,0x34008000,0x31a8b1a8,0x34008000,0xb1a8b1a8,0xb4008000,0xae1f3364,0xb4008000,0x33642e1f,
0x34008000,0x34008000,0xb4008000,0x3400,0xb1a831a8,0xae1f3364,0x31a8b1a8,0xb364ae1f,0xb400,0xb1a8b1a8,0x3400,0x31a8b1a8,
0x31a831a8,0x3364ae1f,0xb1a8b1a8,0x2e1f3364,0x34008000,0x34008000,0x34008000,0xb400,0x3400,0x2e1f3364,0x3400,0x3364ae1f,
0xb4008000,0xb1a831a8,0xb4008000,0x31a831a8,0xb400,0xb364ae1f,0xb400,0xae1f3364,0x34008000,0x34008000,0xb4008000,0x3400,
0x31a831a8,0x33642e1f,0xb1a8b1a8,0xae1f3364,0x3400,0x31a831a8,0xb400,0xb1a831a8,0xb1a831a8,0x2e1f3364,0x31a8b1a8,0xb3642e1f,
0x34008000,0xb4008000,0x34008000,0x3400,0x34008000,0xb3642e1f,0x34008000,0x2e1f3364,0x34008000,0xb1a831a8,0x34008000,0x31a831a8,
0x34008000,0xae1f3364,0x34008000,0x33642e1f,0x34008000,0xb4008000,0xb4008000,0xb400,0x31a8b1a8,0xae1f3364,0xb1a831a8,0xb364ae1f,
0xb400,0x31a831a8,0x3400,0xb1a831a8,0xb1a8b1a8,0x3364ae1f,0x31a831a8,0x2e1f3364,0x34008000,0xb4008000,0x34008000,0x3400,
0xb400,0x2e1f3364,0xb400,0x3364ae1f,0xb4008000,0x31a8b1a8,0xb4008000,0xb1a8b1a8,0x3400,0xb364ae1f,0x3400,0xae1f3364,
0x34008000,0xb4008000,0xb4008000,0xb400,0xb1a8b1a8,0x33642e1f,0x31a831a8,0xae1f3364,0x3400,0xb1a8b1a8,0xb400,0x31a8b1a8,
0x31a8b1a8,0x2e1f3364,0xb1a831a8,0xb3642e1f,0x34008000,0xb4008000,0x34008000,0x3400,0xb4008000,0x3364ae1f,0xb4008000,0xae1fb364,
0x34008000,0xb1a831a8,0x34008000,0x31a831a8,0xb4008000,0x2e1fb364,0xb4008000,0xb364ae1f,0x34008000,0xb4008000,0xb4008000,0xb400,
0xb1a831a8,0x2e1fb364,0x31a8b1a8,0x33642e1f,0xb400,0x31a831a8,0x3400,0xb1a831a8,0x31a831a8,0xb3642e1f,0xb1a8b1a8,0xae1fb364,
0x34008000,0xb4008000,0x34008000,0x3400,0x3400,0xae1fb364,0x3400,0xb3642e1f,0xb4008000,0x31a8b1a8,0xb4008000,0xb1a8b1a8,
0xb400,0x33642e1f,0xb400,0x2e1fb364,0x34008000,0xb4008000,0xb4008000,0xb400,0x31a831a8,0xb364ae1f,0xb1a8b1a8,0x2e1fb364,
0x3400,0xb1a8b1a8,0xb400,0x31a8b1a8,0xb1a831a8,0xae1fb364,0x31a8b1a8,0x3364ae1f,0x34003400,0x31a83400,0x34003400,0x2e1f3364,
0x34003400,0xb1a80000,0x34003400,0xb364ae1f,0x34003400,0xb1a8b400,0x34003400,0xae1fb364,0x34003400,0x31a80000,0x34003400,0x33642e1f,
0x3400,0xb1a83400,0xb1a831a8,0xb3642e1f,0xb400,0x31a80000,0x31a8b1a8,0xae1f3364,0x3400,0x31a8b400,0xb1a831a8,0x3364ae1f,
0xb400,0xb1a80000,0x31a8b1a8,0x2e1fb364,0xb4003400,0xb1a83400,0x0,0x3364ae1f,0xb4003400,0x31a80000,0x0,0x2e1fb364,
0xb4003400,0x31a8b400,0x0,0xb3642e1f,0xb4003400,0xb1a80000,0x0,0xae1f3364,0x3400,0x31a83400,0x31a8b1a8,0xae1fb364,
0xb400,0xb1a80000,0xb1a831a8,0x33642e1f,0x3400,0xb1a8b400,0x31a8b1a8,0x2e1f3364,0xb400,0x31a80000,0xb1a831a8,0xb364ae1f,
0x34003400,0x31a83400,0xb400b400,0xae1fb364,0x34003400,0xb1a80000,0xb400b400,0x33642e1f,0x34003400,0xb1a8b400,0xb400b400,0x2e1f3364,
0x34003400,0x31a80000,0xb400b400,0xb364ae1f,0x3400,0xb1a83400,0x31a8b1a8,0x3364ae1f,0xb400,0x31a80000,0xb1a831a8,0x2e1fb364,
0x3400,0x31a8b400,0x31a8b1a8,0xb3642e1f,0xb400,0xb1a80000,0xb1a831a8,0xae1f3364,0xb4003400,0xb1a83400,0x0,0xb3642e1f,
0xb4003400,0x31a80000,0x0,0xae1f3364,0xb4003400,0x31a8b400,0x0,0x3364ae1f,0xb4003400,0xb1a80000,0x0,0x2e1fb364,
0x3400,0x31a83400,0xb1a831a8,0x2e1f3364,0xb400,0xb1a80000,0x31a8b1a8,0xb364ae1f,0x3400,0xb1a8b400,0xb1a831a8,0xae1fb364,
0xb400,0x31a80000,0x31a8b1a8,0x33642e1f,0x0,0x31a80000,0x0,0x33642e1f,0x0,0x31a83400,0x0,0x2e1f3364,
0x0,0xb1a80000,0x0,0xb364ae1f,0x0,0xb1a8b400,0x0,0xae1fb364,0x34000000,0x31a80000,0x31a831a8,0xae1f3364,
0xb4000000,0x31a8b400,0xb1a8b1a8,0x3364ae1f,0x34000000,0xb1a80000,0x31a831a8,0x2e1fb364,0xb4000000,0xb1a83400,0xb1a8b1a8,0xb3642e1f,
0x0,0xb1a80000,0xb4003400,0xae1f3364,0x0,0xb1a83400,0xb4003400,0x3364ae1f,0x0,0x31a80000,0xb4003400,0x2e1fb364,
0x0,0x31a8b400,0xb4003400,0xb3642e1f,0xb4000000,0xb1a80000,0x31a831a8,0x33642e1f,0x34000000,0xb1a8b400,0xb1a8b1a8,0x2e1f3364,
0xb4000000,0x31a80000,0x31a831a8,0xb364ae1f,0x34000000,0x31a83400,0xb1a8b1a8,0xae1fb364,0x0,0x31a80000,0x0,0xb364ae1f,
0x0,0x31a83400,0x0,0xae1fb364,0x0,0xb1a80000,0x0,0x33642e1f,0x0,0xb1a8b400,0x0,0x2e1f3364,
0x34000000,0x31a80000,0xb1a8b1a8,0x2e1fb364,0xb4000000,0x31a8b400,0x31a831a8,0xb3642e1f,0x34000000,0xb1a80000,0xb1a8b1a8,0xae1f3364,
0xb4000000,0xb1a83400,0x31a831a8,0x3364ae1f,0x0,0xb1a80000,0x3400b400,0x2e1fb364,0x0,0xb1a83400,0x3400b400,0xb3642e1f,
0x0,0x31a80000,0x3400b400,0xae1f3364,0x0,0x31a8b400,0x3400b400,0x3364ae1f,0xb4000000,0xb1a80000,0xb1a8b1a8,0xb364ae1f,
0x34000000,0xb1a8b400,0x31a831a8,0xae1fb364,0xb4000000,0x31a80000,0xb1a8b1a8,0x33642e1f,0x34000000,0x31a83400,0x31a831a8,0x2e1f3364,
0x80008000,0xb1a88000,0x80008000,0xb364ae1f,0x80008000,0xb1a8b400,0x80008000,0xae1fb364,0x80008000,0x31a88000,0x80008000,0x33642e1f,
0x80008000,0x31a83400,0x80008000,0x2e1f3364,0xb4008000,0xb1a88000,0xb1a8b1a8,0x2e1fb364,0x34008000,0xb1a83400,0x31a831a8,0xb3642e1f,
0xb4008000,0x31a88000,0xb1a8b1a8,0xae1f3364,0x34008000,0x31a8b400,0x31a831a8,0x3364ae1f,0x80008000,0x31a88000,0x3400b400,0x2e1fb364,
0x80008000,0x31a8b400,0x3400b400,0xb3642e1f,0x80008000,0xb1a88000,0x3400b400,0xae1f3364,0x80008000,0xb1a83400,0x3400b400,0x3364ae1f,
0x34008000,0x31a88000,0xb1a8b1a8,0xb364ae1f,0xb4008000,0x31a83400,0x31a831a8,0xae1fb364,0x34008000,0xb1a88000,0xb1a8b1a8,0x33642e1f,
0xb4008000,0xb1a8b400,0x31a831a8,0x2e1f3364,0x80008000,0xb1a88000,0x80008000,0x33642e1f,0x80008000,0xb1a8b400,0x80008000,0x2e1f3364,
0x80008000,0x31a88000,0x80008000,0xb364ae1f,0x80008000,0x31a83400,0x80008000,0xae1fb364,0xb4008000,0xb1a88000,0x31a831a8,0xae1f3364,
0x34008000,0xb1a83400,0xb1a8b1a8,0x3364ae1f,0xb4008000,0x31a88000,0x31a831a8,0x2e1fb364,0x34008000,0x31a8b400,0xb1a8b1a8,0xb3642e1f,
0x80008000,0x31a88000,0xb4003400,0xae1f3364,0x80008000,0x31a8b400,0xb4003400,0x3364ae1f,0x80008000,0xb1a88000,0xb4003400,0x2e1fb364,
0x80008000,0xb1a83400,0xb4003400,0xb3642e1f,0x34008000,0x31a88000,0x31a831a8,0x33642e1f,0xb4008000,0x31a83400,0xb1a8b1a8,0x2e1f3364,
0x34008000,0xb1a88000,0x31a831a8,0xb364ae1f,0xb4008000,0xb1a8b400,0xb1a8b1a8,0xae1fb364,0x3f800000,0x3f800000,0x3f800000,0x3f7fb10f,
0x3f800000,0x3f800000,0x3f7ec46d,0x3f7d3aac,0x3f800000,0x3f800000,0x3f7b14be,0x3f7853f8,0x3f800000,0x3f800000,0x3f74fa0b,0x3f710908,
0x3f800000,0x3f7ec46d,0x3f800000,0x3f7d3aac,0x3f7b14be,0x3f74fa0b,0x3f74fa0b,0x3f676bd8,0x3f6c835e,0x3f61c598,0x3f54db31,0x3f3daef9,
0x3f54db31,0x3f45e403,0x3f226799,0x3f039c3d,0x3f800000,0x3f7b14be,0x3f800000,0x3f7853f8,0x3f6c835e,0x3f54db31,0x3f61c598,0x3f3daef9,
0x3f3504f3,0x3f0e39da,0x3f0e39da,0x3eac7cd4,0x3ec3ef15,0x3e47c5c2,0x3dc8bd36,0xbe164083,0x3f800000,0x3f74fa0b,0x3f800000,0x3f710908,
0x3f54db31,0x3f226799,0x3f45e403,0x3f039c3d,0x3ec3ef15,0x3dc8bd36,0x3e47c5c2,0xbe164083,0xbe47c5c2,0xbef15aea,0xbef15aea,0xbf3daef9,
0x3f800000,0x3f6c835e,0x3f800000,0x3f676bd8,0x3f3504f3,0x3ec3ef15,0x3f226799,0x3e78cfcc,0x0,0xbec3ef15,0xbe47c5c2,0xbf187fc0,
0xbf3504f3,0xbf6c835e,0xbf61c598,0xbf7fb10f,0x3f800000,0x3f61c598,0x3f800000,0x3f5b941a,0x3f0e39da,0x3dc8bd36,0x3ef15aea,0xbd48fb30,
0xbec3ef15,0xbf45e403,0xbf0e39da,0xbf676bd8,0xbf7b14be,0xbf74fa0b,0xbf7ec46d,0xbf4d9f02,0x3f800000,0x3f54db31,0x3f800000,0x3f4d9f02,
0x3ec3ef15,0xbe47c5c2,0x3e94a031,0xbeac7cd4,0xbf3504f3,0xbf7b14be,0xbf54db31,0xbf7fb10f,0xbf6c835e,0xbf0e39da,0xbf45e403,0xbe78cfcc,
0x3f800000,0x3f45e403,0x3f800000,0x3f3daef9,0x3e47c5c2,0xbef15aea,0x3dc8bd36,0xbf187fc0,0xbf6c835e,0xbf74fa0b,0xbf7b14be,0xbf5b941a,
0xbf0e39da,0x3dc8bd36,0xbe94a031,0x3edae880,0x3f800000,0x3f800000,0x3f7fec43,0x3f7f4e6d,0x3f800000,0x3f800000,0x3f7e1324,0x3f7c3b28,
0x3f800000,0x3f800000,0x3f79c79d,0x3f76ba07,0x3f800000,0x3f800000,0x3f731447,0x3f6ed89e,0x3f7fb10f,0x3f7d3aac,0x3f7f4e6d,0x3f79c79d,
0x3f7853f8,0x3f710908,0x3f6ed89e,0x3f5ebe05,0x3f676bd8,0x3f5b941a,0x3f49d112,0x3f3085bb,0x3f4d9f02,0x3f3daef9,0x3f13682a,0x3ee63375,
0x3f7ec46d,0x3f74fa0b,0x3f7e1324,0x3f6ed89e,0x3f61c598,0x3f45e403,0x3f514d3d,0x3f273656,0x3f226799,0x3ef15aea,0x3ee63375,0x3e605c13,
0x3e94a031,0x3dc8bd36,0xbcc90ab0,0xbe888e93,0x3f7d3aac,0x3f676bd8,0x3f7c3b28,0x3f5ebe05,0x3f3daef9,0x3f039c3d,0x3f273656,0x3eb8442a,
0x3e78cfcc,0xbd48fb30,0x3cc90ab0,0xbea09ae5,0xbeac7cd4,0xbf187fc0,0xbf1d7fd1,0xbf584853,0x3f7b14be,0x3f54db31,0x3f79c79d,0x3f49d112,
0x3f0e39da,0x3e47c5c2,0x3ee63375,0x3cc90ab0,0xbe47c5c2,0xbf0e39da,0xbecf7bca,0xbf41d870,0xbf54db31,0xbf7b14be,0xbf76ba07,0xbf7c3b28,
0x3f7853f8,0x3f3daef9,0x3f76ba07,0x3f3085bb,0x3eac7cd4,0xbe164083,0x3e605c13,0xbea09ae5,0xbf187fc0,0xbf676bd8,0xbf41d870,0xbf7c3b28,
0xbf7fb10f,0xbf5b941a,0xbf6ed89e,0xbf1d7fd1,0x3f74fa0b,0x3f226799,0x3f731447,0x3f13682a,0x3dc8bd36,0xbef15aea,0xbcc90ab0,0xbf1d7fd1,
0xbf61c598,0xbf7ec46d,0xbf76ba07,0xbf6ed89e,0xbf45e403,0xbe94a031,0xbf08f59b,0x3d96a905,0x3f710908,0x3f039c3d,0x3f6ed89e,0x3ee63375,
0xbe164083,0xbf3daef9,0xbe888e93,0xbf584853,0xbf7fb10f,0xbf4d9f02,0xbf7c3b28,0xbf1d7fd1,0xbe78cfcc,0x3edae880,0x3d96a905,0x3f396842,
0x0,0x0,0x0,0x3d48fb30,0x0,0x0,0x3dc8bd36,0x3e164083,0x0,0x0,0x3e47c5c2,0x3e78cfcc,
0x0,0x0,0x3e94a031,0x3eac7cd4,0x0,0x3dc8bd36,0x0,0x3e164083,0x3e47c5c2,0x3e94a031,0x3e94a031,0x3edae880,
0x3ec3ef15,0x3ef15aea,0x3f0e39da,0x3f2beb4a,0x3f0e39da,0x3f226799,0x3f45e403,0x3f5b941a,0x0,0x3e47c5c2,0x0,0x3e78cfcc,
0x3ec3ef15,0x3f0e39da,0x3ef15aea,0x3f2beb4a,0x3f3504f3,0x3f54db31,0x3f54db31,0x3f710908,0x3f6c835e,0x3f7b14be,0x3f7ec46d,0x3f7d3aac,
0x0,0x3e94a031,0x0,0x3eac7cd4,0x3f0e39da,0x3f45e403,0x3f226799,0x3f5b941a,0x3f6c835e,0x3f7ec46d,0x3f7b14be,0x3f7d3aac,
0x3f7b14be,0x3f61c598,0x3f61c598,0x3f2beb4a,0x0,0x3ec3ef15,0x0,0x3edae880,0x3f3504f3,0x3f6c835e,0x3f45e403,0x3f7853f8,
0x3f800000,0x3f6c835e,0x3f7b14be,0x3f4d9f02,0x3f3504f3,0x3ec3ef15,0x3ef15aea,0x3d48fb30,0x0,0x3ef15aea,0x0,0x3f039c3d,
0x3f54db31,0x3f7ec46d,0x3f61c598,0x3f7fb10f,0x3f6c835e,0x3f226799,0x3f54db31,0x3edae880,0x3e47c5c2,0xbe94a031,0xbdc8bd36,0xbf187fc0,
0x0,0x3f0e39da,0x0,0x3f187fc0,0x3f6c835e,0x3f7b14be,0x3f74fa0b,0x3f710908,0x3f3504f3,0x3e47c5c2,0x3f0e39da,0xbd48fb30,
0xbec3ef15,0xbf54db31,0xbf226799,0xbf7853f8,0x0,0x3f226799,0x0,0x3f2beb4a,0x3f7b14be,0x3f61c598,0x3f7ec46d,0x3f4d9f02,
0x3ec3ef15,0xbe94a031,0x3e47c5c2,0xbf039c3d,0xbf54db31,0xbf7ec46d,0xbf74fa0b,0xbf676bd8,0x0,0x0,0x3cc90ab0,0x3d96a905,
0x0,0x0,0x3dfab273,0x3e2f10a2,0x0,0x0,0x3e605c13,0x3e888e93,0x0,0x0,0x3ea09ae5,0x3eb8442a,
0x3d48fb30,0x3e164083,0x3d96a905,0x3e605c13,0x3e78cfcc,0x3eac7cd4,0x3eb8442a,0x3efc5d27,0x3edae880,0x3f039c3d,0x3f1d7fd1,0x3f396842,
0x3f187fc0,0x3f2beb4a,0x3f514d3d,0x3f64aa59,0x3dc8bd36,0x3e94a031,0x3dfab273,0x3eb8442a,0x3ef15aea,0x3f226799,0x3f13682a,0x3f41d870,
0x3f45e403,0x3f61c598,0x3f64aa59,0x3f79c79d,0x3f74fa0b,0x3f7ec46d,0x3f7fec43,0x3f76ba07,0x3e164083,0x3edae880,0x3e2f10a2,0x3efc5d27,
0x3f2beb4a,0x3f5b941a,0x3f41d870,0x3f6ed89e,0x3f7853f8,0x3f7fb10f,0x3f7fec43,0x3f731447,0x3f710908,0x3f4d9f02,0x3f49d112,0x3f08f59b,
0x3e47c5c2,0x3f0e39da,0x3e605c13,0x3f1d7fd1,0x3f54db31,0x3f7b14be,0x3f64aa59,0x3f7fec43,0x3f7b14be,0x3f54db31,0x3f6a09a7,0x3f273656,
0x3f0e39da,0x3e47c5c2,0x3e888e93,0xbe2f10a2,0x3e78cfcc,0x3f2beb4a,0x3e888e93,0x3f396842,0x3f710908,0x3f7d3aac,0x3f79c79d,0x3f731447,
0x3f4d9f02,0x3edae880,0x3f273656,0x3e2f10a2,0xbd48fb30,0xbf039c3d,0xbeb8442a,0xbf49d112,0x3e94a031,0x3f45e403,0x3ea09ae5,0x3f514d3d,
0x3f7ec46d,0x3f61c598,0x3f7fec43,0x3f49d112,0x3ef15aea,0xbdc8bd36,0x3e888e93,0xbeb8442a,0xbf226799,0xbf74fa0b,0xbf584853,0xbf7f4e6d,
0x3eac7cd4,0x3f5b941a,0x3eb8442a,0x3f64aa59,0x3f7d3aac,0x3f2beb4a,0x3f76ba07,0x3f08f59b,0x3d48fb30,0xbf187fc0,0xbe2f10a2,0xbf49d112,
0xbf7853f8,0xbf676bd8,0xbf7f4e6d,0xbf3085bb,0x3800,0x38008000,0x3800,0x38008000,0x3800,0x38008000,0x3800,0x38008000,
0x3800,0x38008000,0x3800,0x38008000,0x3800,0x38008000,0x3800,0x38008000,0x3800,0x38008000,0xb800,0xb8008000,
0x35a835a8,0x35a8b5a8,0xb5a8b5a8,0xb5a835a8,0x38000000,0xb800,0xb8000000,0x3800,0x35a8b5a8,0xb5a8b5a8,0xb5a835a8,0x35a835a8,
0x3800,0x38008000,0x3800,0x38008000,0x38000000,0xb800,0x38000000,0xb800,0xb800,0xb8008000,0xb800,0xb8008000,
0xb8000000,0x3800,0xb8000000,0x3800,0x3800,0x38008000,0xb800,0xb8008000,0x35a8b5a8,0xb5a8b5a8,0xb5a835a8,0x35a835a8,
0xb8000000,0x3800,0x38000000,0xb800,0x35a835a8,0x35a8b5a8,0xb5a8b5a8,0xb5a835a8,0x3800,0x38008000,0x3800,0x38008000,
0xb800,0xb8008000,0xb800,0xb8008000,0x3800,0x38008000,0x3800,0x38008000,0xb800,0xb8008000,0xb800,0xb8008000,
0x3800,0x38008000,0xb800,0xb8008000,0xb5a8b5a8,0xb5a835a8,0x35a835a8,0x35a8b5a8,0x38000000,0xb800,0xb8000000,0x3800,
0xb5a835a8,0x35a835a8,0x35a8b5a8,0xb5a8b5a8,0x3800,0x38008000,0x3800,0x38008000,0xb8000000,0x3800,0xb8000000,0x3800,
0xb800,0xb8008000,0xb800,0xb8008000,0x38000000,0xb800,0x38000000,0xb800,0x3800,0x38008000,0xb800,0xb8008000,
0xb5a835a8,0x35a835a8,0x35a8b5a8,0xb5a8b5a8,0xb8000000,0x3800,0x38000000,0xb800,0xb5a8b5a8,0xb5a835a8,0x35a835a8,0x35a8b5a8,
0x80003800,0xb8008000,0x80003800,0xb8008000,0x80003800,0xb8008000,0x80003800,0xb8008000,0x80003800,0xb8008000,0x80003800,0xb8008000,
0x80003800,0xb8008000,0x80003800,0xb8008000,0x80003800,0xb8008000,0x8000b800,0x38008000,0xb5a835a8,0xb5a8b5a8,0x35a8b5a8,0x35a835a8,
0xb8000000,0x8000b800,0x38000000,0x80003800,0xb5a8b5a8,0x35a8b5a8,0x35a835a8,0xb5a835a8,0x80003800,0xb8008000,0x80003800,0xb8008000,
0xb8000000,0x8000b800,0xb8000000,0x8000b800,0x8000b800,0x38008000,0x8000b800,0x38008000,0x38000000,0x80003800,0x38000000,0x80003800,
0x80003800,0xb8008000,0x8000b800,0x38008000,0xb5a8b5a8,0x35a8b5a8,0x35a835a8,0xb5a835a8,0x38000000,0x80003800,0xb8000000,0x8000b800,
0xb5a835a8,0xb5a8b5a8,0x35a8b5a8,0x35a835a8,0x80003800,0xb8008000,0x80003800,0xb8008000,0x8000b800,0x38008000,0x8000b800,0x38008000,
0x80003800,0xb8008000,0x80003800,0xb8008000,0x8000b800,0x38008000,0x8000b800,0x38008000,0x80003800,0xb8008000,0x8000b800,0x38008000,
0x35a8b5a8,0x35a835a8,0xb5a835a8,0xb5a8b5a8,0xb8000000,0x8000b800,0x38000000,0x80003800,0x35a835a8,0xb5a835a8,0xb5a8b5a8,0x35a8b5a8,
0x80003800,0xb8008000,0x80003800,0xb8008000,0x38000000,0x80003800,0x38000000,0x80003800,0x8000b800,0x38008000,0x8000b800,0x38008000,
0xb8000000,0x8000b800,0xb8000000,0x8000b800,0x80003800,0xb8008000,0x8000b800,0x38008000,0x35a835a8,0xb5a835a8,0xb5a8b5a8,0x35a8b5a8,
0x38000000,0x80003800,0xb8000000,0x8000b800,0x35a8b5a8,0x35a835a8,0xb5a835a8,0xb5a8b5a8,0x80003400,0x34000000,0x80003400,0x34000000,
0x80003400,0x34000000,0x80003400,0x34000000,0x80003400,0x34000000,0x80003400,0x34000000,0x80003400,0x34000000,0x80003400,0x34000000,
0x80003400,0x34000000,0x8000b400,0xb4000000,0xb1a831a8,0x31a831a8,0x31a8b1a8,0xb1a8b1a8,0xb4000000,0x3400,0x34000000,0xb400,
0xb1a8b1a8,0xb1a831a8,0x31a831a8,0x31a8b1a8,0x80003400,0x34000000,0x80003400,0x34000000,0xb4000000,0x3400,0xb4000000,0x3400,
0x8000b400,0xb4000000,0x8000b400,0xb4000000,0x34000000,0xb400,0x34000000,0xb400,0x80003400,0x34000000,0x8000b400,0xb4000000,
0xb1a8b1a8,0xb1a831a8,0x31a831a8,0x31a8b1a8,0x34000000,0xb400,0xb4000000,0x3400,0xb1a831a8,0x31a831a8,0x31a8b1a8,0xb1a8b1a8,
0x80003400,0x34000000,0x80003400,0x34000000,0x8000b400,0xb4000000,0x8000b400,0xb4000000,0x80003400,0x34000000,0x80003400,0x34000000,
0x8000b400,0xb4000000,0x8000b400,0xb4000000,0x80003400,0x34000000,0x8000b400,0xb4000000,0x31a8b1a8,0xb1a8b1a8,0xb1a831a8,0x31a831a8,
0xb4000000,0x3400,0x34000000,0xb400,0x31a831a8,0x31a8b1a8,0xb1a8b1a8,0xb1a831a8,0x80003400,0x34000000,0x80003400,0x34000000,
0x34000000,0xb400,0x34000000,0xb400,0x8000b400,0xb4000000,0x8000b400,0xb4000000,0xb4000000,0x3400,0xb4000000,0x3400,
0x80003400,0x34000000,0x8000b400,0xb4000000,0x31a831a8,0x31a8b1a8,0xb1a8b1a8,0xb1a831a8,0x34000000,0xb400,0xb4000000,0x3400,
0x31a8b1a8,0xb1a8b1a8,0xb1a831a8,0x31a831a8,0x80003400,0xb4008000,0x80003400,0xb4008000,0x80003400,0xb4008000,0x80003400,0xb4008000,
0x80003400,0xb4008000,0x80003400,0xb4008000,0x80003400,0xb4008000,0x80003400,0xb4008000,0x80003400,0xb4008000,0x8000b400,0x34008000,
0xb1a831a8,0xb1a8b1a8,0x31a8b1a8,0x31a831a8,0xb4000000,0x8000b400,0x34000000,0x80003400,0xb1a8b1a8,0x31a8b1a8,0x31a831a8,0xb1a831a8,
0x80003400,0xb4008000,0x80003400,0xb4008000,0xb4000000,0x8000b400,0xb4000000,0x8000b400,0x8000b400,0x34008000,0x8000b400,0x34008000,
0x34000000,0x80003400,0x34000000,0x80003400,0x80003400,0xb4008000,0x8000b400,0x34008000,0xb1a8b1a8,0x31a8b1a8,0x31a831a8,0xb1a831a8,
0x34000000,0x80003400,0xb4000000,0x8000b400,0xb1a831a8,0xb1a8b1a8,0x31a8b1a8,0x31a831a8,0x80003400,0xb4008000,0x80003400,0xb4008000,
0x8000b400,0x34008000,0x8000b400,0x34008000,0x80003400,0xb4008000,0x80003400,0xb4008000,0x8000b400,0x34008000,0x8000b400,0x34008000,
0x80003400,0xb4008000,0x8000b400,0x34008000,0x31a8b1a8,0x31a831a8,0xb1a831a8,0xb1a8b1a8,0xb4000000,0x8000b400,0x34000000,0x80003400,
0x31a831a8,0xb1a831a8,0xb1a8b1a8,0x31a8b1a8,0x80003400,0xb4008000,0x80003400,0xb4008000,0x34000000,0x80003400,0x34000000,0x80003400,
0x8000b400,0x34008000,0x8000b400,0x34008000,0xb4000000,0x8000b400,0xb4000000,0x8000b400,0x80003400,0xb4008000,0x8000b400,0x34008000,
0x31a831a8,0xb1a831a8,0xb1a8b1a8,0x31a8b1a8,0x34000000,0x80003400,0xb4000000,0x8000b400,0x31a8b1a8,0x31a831a8,0xb1a831a8,0xb1a8b1a8,
};
__device__ const __align__(16) uint32_t TAB_P3[1408] = {
0x80003400,0x80003400,0x80003400,0xb4000000,0x80003400,0xae1f3364,0x80003400,0xb364ae1f,0x80003400,0xb1a831a8,0x80003400,0xb1a8b1a8,
0x80003400,0xb3642e1f,0x80003400,0xae1fb364,0x80003400,0x80003400,0x8000b400,0x34000000,0xb1a831a8,0xb3642e1f,0x31a8b1a8,0x2e1f3364,
0xb4000000,0xb1a8b1a8,0x34000000,0xb1a831a8,0xb1a8b1a8,0x2e1fb364,0x31a831a8,0xb364ae1f,0x80003400,0x80003400,0x80003400,0xb4000000,
0xb4000000,0xb364ae1f,0xb4000000,0x2e1fb364,0x8000b400,0x31a8b1a8,0x8000b400,0x31a831a8,0x34000000,0x2e1f3364,0x34000000,0xb3642e1f,
0x80003400,0x80003400,0x8000b400,0x34000000,0xb1a8b1a8,0xae1fb364,0x31a831a8,0xb3642e1f,0x34000000,0x31a831a8,0xb4000000,0x31a8b1a8,
0xb1a831a8,0xb364ae1f,0x31a8b1a8,0xae1f3364,0x80003400,0x80003400,0x80003400,0xb4000000,0x8000b400,0x2e1fb364,0x8000b400,0x33642e1f,
0x80003400,0xb1a831a8,0x80003400,0xb1a8b1a8,0x8000b400,0x3364ae1f,0x8000b400,0x2e1f3364,0x80003400,0x80003400,0x8000b400,0x34000000,
0x31a8b1a8,0x3364ae1f,0xb1a831a8,0xae1fb364,0xb4000000,0xb1a8b1a8,0x34000000,0xb1a831a8,0x31a831a8,0xae1f3364,0xb1a8b1a8,0x33642e1f,
0x80003400,0x80003400,0x80003400,0xb4000000,0x34000000,0x33642e1f,0x34000000,0xae1f3364,0x8000b400,0x31a8b1a8,0x8000b400,0x31a831a8,
0xb4000000,0xae1fb364,0xb4000000,0x3364ae1f,0x80003400,0x80003400,0x8000b400,0x34000000,0x31a831a8,0x2e1f3364,0xb1a8b1a8,0x3364ae1f,
0x34000000,0x31a831a8,0xb4000000,0x31a8b1a8,0x31a8b1a8,0x33642e1f,0xb1a831a8,0x2e1fb364,0x80003400,0x8000b400,0x80003400,0x34000000,
0x80003400,0x2e1fb364,0x80003400,0x33642e1f,0x80003400,0x31a8b1a8,0x80003400,0x31a831a8,0x80003400,0x3364ae1f,0x80003400,0x2e1f3364,
0x80003400,0x8000b400,0x8000b400,0xb4000000,0xb1a831a8,0x3364ae1f,0x31a8b1a8,0xae1fb364,0xb4000000,0x31a831a8,0x34000000,0x31a8b1a8,
0xb1a8b1a8,0xae1f3364,0x31a831a8,0x33642e1f,0x80003400,0x8000b400,0x80003400,0x34000000,0xb4000000,0x33642e1f,0xb4000000,0xae1f3364,
0x8000b400,0xb1a831a8,0x8000b400,0xb1a8b1a8,0x34000000,0xae1fb364,0x34000000,0x3364ae1f,0x80003400,0x8000b400,0x8000b400,0xb4000000,
0xb1a8b1a8,0x2e1f3364,0x31a831a8,0x3364ae1f,0x34000000,0xb1a8b1a8,0xb4000000,0xb1a831a8,0xb1a831a8,0x33642e1f,0x31a8b1a8,0x2e1fb364,
0x80003400,0x8000b400,0x80003400,0x34000000,0x8000b400,0xae1f3364,0x8000b400,0xb364ae1f,0x80003400,0x31a8b1a8,0x80003400,0x31a831a8,
0x8000b400,0xb3642e1f,0x8000b400,0xae1fb364,0x80003400,0x8000b400,0x8000b400,0xb4000000,0x31a8b1a8,0xb3642e1f,0xb1a831a8,0x2e1f3364,
0xb4000000,0x31a831a8,0x34000000,0x31a8b1a8,0x31a831a8,0x2e1fb364,0xb1a8b1a8,0xb364ae1f,0x80003400,0x8000b400,0x80003400,0x34000000,
0x34000000,0xb364ae1f,0x34000000,0x2e1fb364,0x8000b400,0xb1a831a8,0x8000b400,0xb1a8b1a8,0xb4000000,0x2e1f3364,0xb4000000,0xb3642e1f,
0x80003400,0x8000b400,0x8000b400,0xb4000000,0x31a831a8,0xae1fb364,0xb1a8b1a8,0xb3642e1f,0x34000000,0xb1a8b1a8,0xb4000000,0xb1a831a8,
0x31a8b1a8,0xb364ae1f,0xb1a831a8,0xae1f3364,0x34000000,0x34000000,0x34000000,0x3400,0x34000000,0x33642e1f,0x34000000,0xae1f3364,
0x34000000,0x31a831a8,0x34000000,0xb1a831a8,0x34000000,0x2e1f3364,0x34000000,0xb3642e1f,0x34000000,0x34000000,0xb4000000,0xb400,
0x31a831a8,0x2e1f3364,0xb1a8b1a8,0x3364ae1f,0x3400,0xb1a831a8,0xb400,0x31a831a8,0xb1a831a8,0xb364ae1f,0x31a8b1a8,0xae1f3364,
0x34000000,0x34000000,0x34000000,0x3400,0x3400,0xae1f3364,0x3400,0xb364ae1f,0xb4000000,0xb1a8b1a8,0xb4000000,0x31a8b1a8,
0xb400,0x3364ae1f,0xb400,0x2e1f3364,0x34000000,0x34000000,0xb4000000,0xb400,0xb1a831a8,0xb3642e1f,0x31a8b1a8,0x2e1f3364,
0xb400,0x31a8b1a8,0x3400,0xb1a8b1a8,0x31a831a8,0xae1f3364,0xb1a8b1a8,0x33642e1f,0x34000000,0x34000000,0x34000000,0x3400,
0xb4000000,0xb364ae1f,0xb4000000,0x2e1fb364,0x34000000,0x31a831a8,0x34000000,0xb1a831a8,0xb4000000,0xae1fb364,0xb4000000,0x3364ae1f,
0x34000000,0x34000000,0xb4000000,0xb400,0xb1a8b1a8,0xae1fb364,0x31a831a8,0xb3642e1f,0x3400,0xb1a831a8,0xb400,0x31a831a8,
0x31a8b1a8,0x33642e1f,0xb1a831a8,0x2e1fb364,0x34000000,0x34000000,0x34000000,0x3400,0xb400,0x2e1fb364,0xb400,0x33642e1f,
0xb4000000,0xb1a8b1a8,0xb4000000,0x31a8b1a8,0x3400,0xb3642e1f,0x3400,0xae1fb364,0x34000000,0x34000000,0xb4000000,0xb400,
0x31a8b1a8,0x3364ae1f,0xb1a831a8,0xae1fb364,0xb400,0x31a8b1a8,0x3400,0xb1a8b1a8,0xb1a8b1a8,0x2e1fb364,0x31a831a8,0xb364ae1f,
0x34000000,0xb4000000,0x34000000,0xb400,0x34000000,0xb364ae1f,0x34000000,0x2e1fb364,0x34000000,0xb1a8b1a8,0x34000000,0x31a8b1a8,
0x34000000,0xae1fb364,0x34000000,0x3364ae1f,0x34000000,0xb4000000,0xb4000000,0x3400,0x31a831a8,0xae1fb364,0xb1a8b1a8,0xb3642e1f,
0x3400,0x31a8b1a8,0xb400,0xb1a8b1a8,0xb1a831a8,0x33642e1f,0x31a8b1a8,0x2e1fb364,0x34000000,0xb4000000,0x34000000,0xb400,
0x3400,0x2e1fb364,0x3400,0x33642e1f,0xb4000000,0x31a831a8,0xb4000000,0xb1a831a8,0xb400,0xb3642e1f,0xb400,0xae1fb364,
0x34000000,0xb4000000,0xb4000000,0x3400,0xb1a831a8,0x3364ae1f,0x31a8b1a8,0xae1fb364,0xb400,0xb1a831a8,0x3400,0x31a831a8,
0x31a831a8,0x2e1fb364,0xb1a8b1a8,0xb364ae1f,0x34000000,0xb4000000,0x34000000,0xb400,0xb4000000,0x33642e1f,0xb4000000,0xae1f3364,
0x34000000,0xb1a8b1a8,0x34000000,0x31a8b1a8,0xb4000000,0x2e1f3364,0xb4000000,0xb3642e1f,0x34000000,0xb4000000,0xb4000000,0x3400,
0xb1a8b1a8,0x2e1f3364,0x31a831a8,0x3364ae1f,0x3400,0x31a8b1a8,0xb400,0xb1a8b1a8,0x31a8b1a8,0xb364ae1f,0xb1a831a8,0xae1f3364,
0x34000000,0xb4000000,0x34000000,0xb400,0xb400,0xae1f3364,0xb400,0xb364ae1f,0xb4000000,0x31a831a8,0xb4000000,0xb1a831a8,
0x3400,0x3364ae1f,0x3400,0x2e1f3364,0x34000000,0xb4000000,0xb4000000,0x3400,0x31a8b1a8,0xb3642e1f,0xb1a831a8,0x2e1f3364,
0xb400,0xb1a831a8,0x3400,0x31a831a8,0xb1a8b1a8,0xae1f3364,0x31a831a8,0x33642e1f,0x34003400,0xb4003400,0x34003400,0xb4003400,
0x34003400,0xb4003400,0x34003400,0xb4003400,0x34003400,0xb4003400,0x34003400,0xb4003400,0x34003400,0xb4003400,0x34003400,0xb4003400,
0x33643400,0xb3643400,0xb364b400,0x3364b400,0x2e1f31a8,0xae1f31a8,0xae1fb1a8,0x2e1fb1a8,0xae1f0000,0x2e1f0000,0x2e1f0000,0xae1f0000,
0xb364b1a8,0x3364b1a8,0x336431a8,0xb36431a8,0x31a83400,0xb1a83400,0x31a83400,0xb1a83400,0xb1a80000,0x31a80000,0xb1a80000,0x31a80000,
0xb1a8b400,0x31a8b400,0xb1a8b400,0x31a8b400,0x31a80000,0xb1a80000,0x31a80000,0xb1a80000,0x2e1f3400,0xae1f3400,0xae1fb400,0x2e1fb400,
0xb364b1a8,0x3364b1a8,0x336431a8,0xb36431a8,0x33640000,0xb3640000,0xb3640000,0x33640000,0xae1f31a8,0x2e1f31a8,0x2e1fb1a8,0xae1fb1a8,
0x3400,0x3400,0x3400,0x3400,0xb400,0xb400,0xb400,0xb400,0x3400,0x3400,0x3400,0x3400,
0xb400,0xb400,0xb400,0xb400,0xae1f3400,0x2e1f3400,0x2e1fb400,0xae1fb400,0x3364b1a8,0xb364b1a8,0xb36431a8,0x336431a8,
0xb3640000,0x33640000,0x33640000,0xb3640000,0x2e1f31a8,0xae1f31a8,0xae1fb1a8,0x2e1fb1a8,0xb1a83400,0x31a83400,0xb1a83400,0x31a83400,
0x31a80000,0xb1a80000,0x31a80000,0xb1a80000,0x31a8b400,0xb1a8b400,0x31a8b400,0xb1a8b400,0xb1a80000,0x31a80000,0xb1a80000,0x31a80000,
0xb3643400,0x33643400,0x3364b400,0xb364b400,0xae1f31a8,0x2e1f31a8,0x2e1fb1a8,0xae1fb1a8,0x2e1f0000,0xae1f0000,0xae1f0000,0x2e1f0000,
0x3364b1a8,0xb364b1a8,0xb36431a8,0x336431a8,0x0,0x0,0x0,0x0,0x0,0x0,0x0,0x0,
0x0,0x0,0x0,0x0,0x0,0x0,0x0,0x0,0x2e1f0000,0xae1f0000,0xae1f0000,0x2e1f0000,
0x336431a8,0xb36431a8,0xb364b1a8,0x3364b1a8,0x33643400,0xb3643400,0xb364b400,0x3364b400,0x2e1f31a8,0xae1f31a8,0xae1fb1a8,0x2e1fb1a8,
0x31a80000,0xb1a80000,0x31a80000,0xb1a80000,0x31a83400,0xb1a83400,0x31a83400,0xb1a83400,0xb1a80000,0x31a80000,0xb1a80000,0x31a80000,
0xb1a8b400,0x31a8b400,0xb1a8b400,0x31a8b400,0x33640000,0xb3640000,0xb3640000,0x33640000,0xae1f31a8,0x2e1f31a8,0x2e1fb1a8,0xae1fb1a8,
0xae1fb400,0x2e1fb400,0x2e1f3400,0xae1f3400,0x336431a8,0xb36431a8,0xb364b1a8,0x3364b1a8,0x34000000,0xb4000000,0x34000000,0xb4000000,
0xb4000000,0x34000000,0xb4000000,0x34000000,0x34000000,0xb4000000,0x34000000,0xb4000000,0xb4000000,0x34000000,0xb4000000,0x34000000,
0x33640000,0xb3640000,0xb3640000,0x33640000,0xae1fb1a8,0x2e1fb1a8,0x2e1f31a8,0xae1f31a8,0xae1f3400,0x2e1f3400,0x2e1fb400,0xae1fb400,
0x3364b1a8,0xb364b1a8,0xb36431a8,0x336431a8,0x31a80000,0xb1a80000,0x31a80000,0xb1a80000,0x31a8b400,0xb1a8b400,0x31a8b400,0xb1a8b400,
0xb1a80000,0x31a80000,0xb1a80000,0x31a80000,0xb1a83400,0x31a83400,0xb1a83400,0x31a83400,0x2e1f0000,0xae1f0000,0xae1f0000,0x2e1f0000,
0x3364b1a8,0xb364b1a8,0xb36431a8,0x336431a8,0x3364b400,0xb364b400,0xb3643400,0x33643400,0x2e1fb1a8,0xae1fb1a8,0xae1f31a8,0x2e1f31a8,
0x80008000,0x80008000,0x80008000,0x80008000,0x80008000,0x80008000,0x80008000,0x80008000,0x80008000,0x80008000,0x80008000,0x80008000,
0x80008000,0x80008000,0x80008000,0x80008000,0xae1f8000,0x2e1f8000,0x2e1f8000,0xae1f8000,0xb364b1a8,0x3364b1a8,0x336431a8,0xb36431a8,
0xb364b400,0x3364b400,0x33643400,0xb3643400,0xae1fb1a8,0x2e1fb1a8,0x2e1f31a8,0xae1f31a8,0xb1a88000,0x31a88000,0xb1a88000,0x31a88000,
0xb1a8b400,0x31a8b400,0xb1a8b400,0x31a8b400,0x31a88000,0xb1a88000,0x31a88000,0xb1a88000,0x31a83400,0xb1a83400,0x31a83400,0xb1a83400,
0xb3648000,0x33648000,0x33648000,0xb3648000,0x2e1fb1a8,0xae1fb1a8,0xae1f31a8,0x2e1f31a8,0x2e1f3400,0xae1f3400,0xae1fb400,0x2e1fb400,
0xb364b1a8,0x3364b1a8,0x336431a8,0xb36431a8,0xb4008000,0x34008000,0xb4008000,0x34008000,0x34008000,0xb4008000,0x34008000,0xb4008000,
0xb4008000,0x34008000,0xb4008000,0x34008000,0x34008000,0xb4008000,0x34008000,0xb4008000,0xb3648000,0x33648000,0x33648000,0xb3648000,
0x2e1f31a8,0xae1f31a8,0xae1fb1a8,0x2e1fb1a8,0x2e1fb400,0xae1fb400,0xae1f3400,0x2e1f3400,0xb36431a8,0x336431a8,0x3364b1a8,0xb364b1a8,
0xb1a88000,0x31a88000,0xb1a88000,0x31a88000,0xb1a83400,0x31a83400,0xb1a83400,0x31a83400,0x31a88000,0xb1a88000,0x31a88000,0xb1a88000,
0x31a8b400,0xb1a8b400,0x31a8b400,0xb1a8b400,0xae1f8000,0x2e1f8000,0x2e1f8000,0xae1f8000,0xb36431a8,0x336431a8,0x3364b1a8,0xb364b1a8,
0xb3643400,0x33643400,0x3364b400,0xb364b400,0xae1f31a8,0x2e1f31a8,0x2e1fb1a8,0xae1fb1a8,0x3f800000,0x3f800000,0x3f800000,0x3f7fec43,
0x3f800000,0x3f800000,0x3f7fb10f,0x3f7f4e6d,0x3f800000,0x3f800000,0x3f7ec46d,0x3f7e1324,0x3f800000,0x3f800000,0x3f7d3aac,0x3f7c3b28,
0x3f800000,0x3f7fb10f,0x3f800000,0x3f7f4e6d,0x3f7ec46d,0x3f7d3aac,0x3f7d3aac,0x3f79c79d,0x3f7b14be,0x3f7853f8,0x3f74fa0b,0x3f6ed89e,
0x3f74fa0b,0x3f710908,0x3f676bd8,0x3f5ebe05,0x3f800000,0x3f7ec46d,0x3f800000,0x3f7e1324,0x3f7b14be,0x3f74fa0b,0x3f7853f8,0x3f6ed89e,
0x3f6c835e,0x3f61c598,0x3f61c598,0x3f514d3d,0x3f54db31,0x3f45e403,0x3f3daef9,0x3f273656,0x3f800000,0x3f7d3aac,0x3f800000,0x3f7c3b28,
0x3f74fa0b,0x3f676bd8,0x3f710908,0x3f5ebe05,0x3f54db31,0x3f3daef9,0x3f45e403,0x3f273656,0x3f226799,0x3f039c3d,0x3f039c3d,0x3eb8442a,
0x3f800000,0x3f7b14be,0x3f800000,0x3f79c79d,0x3f6c835e,0x3f54db31,0x3f676bd8,0x3f49d112,0x3f3504f3,0x3f0e39da,0x3f226799,0x3ee63375,
0x3ec3ef15,0x3e47c5c2,0x3e78cfcc,0x3cc90ab0,0x3f800000,0x3f7853f8,0x3f800000,0x3f76ba07,0x3f61c598,0x3f3daef9,0x3f5b941a,0x3f3085bb,
0x3f0e39da,0x3eac7cd4,0x3ef15aea,0x3e605c13,0x3dc8bd36,0xbe164083,0xbd48fb30,0xbea09ae5,0x3f800000,0x3f74fa0b,0x3f800000,0x3f731447,
0x3f54db31,0x3f226799,0x3f4d9f02,0x3f13682a,0x3ec3ef15,0x3dc8bd36,0x3e94a031,0xbcc90ab0,0xbe47c5c2,0xbef15aea,0xbeac7cd4,0xbf1d7fd1,
0x3f800000,0x3f710908,0x3f800000,0x3f6ed89e,0x3f45e403,0x3f039c3d,0x3f3daef9,0x3ee63375,0x3e47c5c2,0xbe164083,0x3dc8bd36,0xbe888e93,
0xbef15aea,0xbf3daef9,0xbf187fc0,0xbf584853,0x3f800000,0x3f800000,0x3f7b14be,0x3f79c79d,0x3f800000,0x3f800000,0x3f7853f8,0x3f76ba07,
0x3f800000,0x3f800000,0x3f74fa0b,0x3f731447,0x3f800000,0x3f800000,0x3f710908,0x3f6ed89e,0x3f6c835e,0x3f676bd8,0x3f54db31,0x3f49d112,
0x3f61c598,0x3f5b941a,0x3f3daef9,0x3f3085bb,0x3f54db31,0x3f4d9f02,0x3f226799,0x3f13682a,0x3f45e403,0x3f3daef9,0x3f039c3d,0x3ee63375,
0x3f3504f3,0x3f226799,0x3f0e39da,0x3ee63375,0x3f0e39da,0x3ef15aea,0x3eac7cd4,0x3e605c13,0x3ec3ef15,0x3e94a031,0x3dc8bd36,0xbcc90ab0,
0x3e47c5c2,0x3dc8bd36,0xbe164083,0xbe888e93,0x3ec3ef15,0x3e78cfcc,0x3e47c5c2,0x3cc90ab0,0x3dc8bd36,0xbd48fb30,0xbe164083,0xbea09ae5,
0xbe47c5c2,0xbeac7cd4,0xbef15aea,0xbf1d7fd1,0xbef15aea,0xbf187fc0,0xbf3daef9,0xbf584853,0x0,0xbe47c5c2,0xbe47c5c2,0xbecf7bca,
0xbec3ef15,0xbf0e39da,0xbf187fc0,0xbf41d870,0xbf3504f3,0xbf54db31,0xbf61c598,0xbf76ba07,0xbf6c835e,0xbf7b14be,0xbf7fb10f,0xbf7c3b28,
0xbec3ef15,0xbf187fc0,0xbf0e39da,0xbf41d870,0xbf45e403,0xbf676bd8,0xbf676bd8,0xbf7c3b28,0xbf7b14be,0xbf7fb10f,0xbf7ec46d,0xbf6ed89e,
0xbf74fa0b,0xbf5b941a,0xbf4d9f02,0xbf1d7fd1,0xbf3504f3,0xbf61c598,0xbf54db31,0xbf76ba07,0xbf7b14be,0xbf7ec46d,0xbf7fb10f,0xbf6ed89e,
0xbf6c835e,0xbf45e403,0xbf45e403,0xbf08f59b,0xbf0e39da,0xbe94a031,0xbe78cfcc,0x3d96a905,0xbf6c835e,0xbf7fb10f,0xbf7b14be,0xbf7c3b28,
0xbf74fa0b,0xbf4d9f02,0xbf5b941a,0xbf1d7fd1,0xbf0e39da,0xbe78cfcc,0xbe94a031,0x3d96a905,0x3dc8bd36,0x3edae880,0x3edae880,0x3f396842,
0x0,0x0,0x0,0x3cc90ab0,0x0,0x0,0x3d48fb30,0x3d96a905,0x0,0x0,0x3dc8bd36,0x3dfab273,
0x0,0x0,0x3e164083,0x3e2f10a2,0x0,0x3d48fb30,0x0,0x3d96a905,0x3dc8bd36,0x3e164083,0x3e164083,0x3e605c13,
0x3e47c5c2,0x3e78cfcc,0x3e94a031,0x3eb8442a,0x3e94a031,0x3eac7cd4,0x3edae880,0x3efc5d27,0x0,0x3dc8bd36,0x0,0x3dfab273,
0x3e47c5c2,0x3e94a031,0x3e78cfcc,0x3eb8442a,0x3ec3ef15,0x3ef15aea,0x3ef15aea,0x3f13682a,0x3f0e39da,0x3f226799,0x3f2beb4a,0x3f41d870,
0x0,0x3e164083,0x0,0x3e2f10a2,0x3e94a031,0x3edae880,0x3eac7cd4,0x3efc5d27,0x3f0e39da,0x3f2beb4a,0x3f226799,0x3f41d870,
0x3f45e403,0x3f5b941a,0x3f5b941a,0x3f6ed89e,0x0,0x3e47c5c2,0x0,0x3e605c13,0x3ec3ef15,0x3f0e39da,0x3edae880,0x3f1d7fd1,
0x3f3504f3,0x3f54db31,0x3f45e403,0x3f64aa59,0x3f6c835e,0x3f7b14be,0x3f7853f8,0x3f7fec43,0x0,0x3e78cfcc,0x0,0x3e888e93,
0x3ef15aea,0x3f2beb4a,0x3f039c3d,0x3f396842,0x3f54db31,0x3f710908,0x3f61c598,0x3f79c79d,0x3f7ec46d,0x3f7d3aac,0x3f7fb10f,0x3f731447,
0x0,0x3e94a031,0x0,0x3ea09ae5,0x3f0e39da,0x3f45e403,0x3f187fc0,0x3f514d3d,0x3f6c835e,0x3f7ec46d,0x3f74fa0b,0x3f7fec43,
0x3f7b14be,0x3f61c598,0x3f710908,0x3f49d112,0x0,0x3eac7cd4,0x0,0x3eb8442a,0x3f226799,0x3f5b941a,0x3f2beb4a,0x3f64aa59,
0x3f7b14be,0x3f7d3aac,0x3f7ec46d,0x3f76ba07,0x3f61c598,0x3f2beb4a,0x3f4d9f02,0x3f08f59b,0x0,0x0,0x3e47c5c2,0x3e605c13,
0x0,0x0,0x3e78cfcc,0x3e888e93,0x0,0x0,0x3e94a031,0x3ea09ae5,0x0,0x0,0x3eac7cd4,0x3eb8442a,
0x3ec3ef15,0x3edae880,0x3f0e39da,0x3f1d7fd1,0x3ef15aea,0x3f039c3d,0x3f2beb4a,0x3f396842,0x3f0e39da,0x3f187fc0,0x3f45e403,0x3f514d3d,
0x3f226799,0x3f2beb4a,0x3f5b941a,0x3f64aa59,0x3f3504f3,0x3f45e403,0x3f54db31,0x3f64aa59,0x3f54db31,0x3f61c598,0x3f710908,0x3f79c79d,
0x3f6c835e,0x3f74fa0b,0x3f7ec46d,0x3f7fec43,0x3f7b14be,0x3f7ec46d,0x3f7d3aac,0x3f76ba07,0x3f6c835e,0x3f7853f8,0x3f7b14be,0x3f7fec43,
0x3f7ec46d,0x3f7fb10f,0x3f7d3aac,0x3f731447,0x3f7b14be,0x3f710908,0x3f61c598,0x3f49d112,0x3f61c598,0x3f4d9f02,0x3f2beb4a,0x3f08f59b,
0x3f800000,0x3f7b14be,0x3f7b14be,0x3f6a09a7,0x3f6c835e,0x3f54db31,0x3f4d9f02,0x3f273656,0x3f3504f3,0x3f0e39da,0x3ef15aea,0x3e888e93,
0x3ec3ef15,0x3e47c5c2,0x3d48fb30,0xbe2f10a2,0x3f6c835e,0x3f4d9f02,0x3f54db31,0x3f273656,0x3f226799,0x3edae880,0x3edae880,0x3e2f10a2,
0x3e47c5c2,0xbd48fb30,0xbdc8bd36,0xbeb8442a,0xbe94a031,0xbf039c3d,0xbf187fc0,0xbf49d112,0x3f3504f3,0x3ef15aea,0x3f0e39da,0x3e888e93,
0x3e47c5c2,0xbdc8bd36,0xbd48fb30,0xbeb8442a,0xbec3ef15,0xbf226799,0xbf226799,0xbf584853,0xbf54db31,0xbf74fa0b,0xbf7853f8,0xbf7f4e6d,
0x3ec3ef15,0x3d48fb30,0x3e47c5c2,0xbe2f10a2,0xbe94a031,0xbf187fc0,0xbf039c3d,0xbf49d112,0xbf54db31,0xbf7853f8,0xbf74fa0b,0xbf7f4e6d,
0xbf7ec46d,0xbf676bd8,0xbf676bd8,0xbf3085bb,
};
__device__ const __align__(16) uint32_t TAB_TW[512] = {
0x3f800000,0x0,0x3f7fb10f,0x3d48fb30,0x3f7ec46d,0x3dc8bd36,0x3f7d3aac,0x3e164083,0x3f7b14be,0x3e47c5c2,0x3f7853f8,0x3e78cfcc,
0x3f74fa0b,0x3e94a031,0x3f710908,0x3eac7cd4,0x3f6c835e,0x3ec3ef15,0x3f676bd8,0x3edae880,0x3f61c598,0x3ef15aea,0x3f5b941a,0x3f039c3d,
0x3f54db31,0x3f0e39da,0x3f4d9f02,0x3f187fc0,0x3f45e403,0x3f226799,0x3f3daef9,0x3f2beb4a,0x3f3504f3,0x3f3504f3,0x3f2beb4a,0x3f3daef9,
0x3f226799,0x3f45e403,0x3f187fc0,0x3f4d9f02,0x3f0e39da,0x3f54db31,0x3f039c3d,0x3f5b941a,0x3ef15aea,0x3f61c598,0x3edae880,0x3f676bd8,
0x3ec3ef15,0x3f6c835e,0x3eac7cd4,0x3f710908,0x3e94a031,0x3f74fa0b,0x3e78cfcc,0x3f7853f8,0x3e47c5c2,0x3f7b14be,0x3e164083,0x3f7d3aac,
0x3dc8bd36,0x3f7ec46d,0x3d48fb30,0x3f7fb10f,0x0,0x3f800000,0xbd48fb30,0x3f7fb10f,0xbdc8bd36,0x3f7ec46d,0xbe164083,0x3f7d3aac,
0xbe47c5c2,0x3f7b14be,0xbe78cfcc,0x3f7853f8,0xbe94a031,0x3f74fa0b,0xbeac7cd4,0x3f710908,0xbec3ef15,0x3f6c835e,0xbedae880,0x3f676bd8,
0xbef15aea,0x3f61c598,0xbf039c3d,0x3f5b941a,0xbf0e39da,0x3f54db31,0xbf187fc0,0x3f4d9f02,0xbf226799,0x3f45e403,0xbf2beb4a,0x3f3daef9,
0xbf3504f3,0x3f3504f3,0xbf3daef9,0x3f2beb4a,0xbf45e403,0x3f226799,0xbf4d9f02,0x3f187fc0,0xbf54db31,0x3f0e39da,0xbf5b941a,0x3f039c3d,
0xbf61c598,0x3ef15aea,0xbf676bd8,0x3edae880,0xbf6c835e,0x3ec3ef15,0xbf710908,0x3eac7cd4,0xbf74fa0b,0x3e94a031,0xbf7853f8,0x3e78cfcc,
0xbf7b14be,0x3e47c5c2,0xbf7d3aac,0x3e164083,0xbf7ec46d,0x3dc8bd36,0xbf7fb10f,0x3d48fb30,0xbf800000,0x0,0xbf7fb10f,0xbd48fb30,
0xbf7ec46d,0xbdc8bd36,0xbf7d3aac,0xbe164083,0xbf7b14be,0xbe47c5c2,0xbf7853f8,0xbe78cfcc,0xbf74fa0b,0xbe94a031,0xbf710908,0xbeac7cd4,
0xbf6c835e,0xbec3ef15,0xbf676bd8,0xbedae880,0xbf61c598,0xbef15aea,0xbf5b941a,0xbf039c3d,0xbf54db31,0xbf0e39da,0xbf4d9f02,0xbf187fc0,
0xbf45e403,0xbf226799,0xbf3daef9,0xbf2beb4a,0xbf3504f3,0xbf3504f3,0xbf2beb4a,0xbf3daef9,0xbf226799,0xbf45e403,0xbf187fc0,0xbf4d9f02,
0xbf0e39da,0xbf54db31,0xbf039c3d,0xbf5b941a,0xbef15aea,0xbf61c598,0xbedae880,0xbf676bd8,0xbec3ef15,0xbf6c835e,0xbeac7cd4,0xbf710908,
0xbe94a031,0xbf74fa0b,0xbe78cfcc,0xbf7853f8,0xbe47c5c2,0xbf7b14be,0xbe164083,0xbf7d3aac,0xbdc8bd36,0xbf7ec46d,0xbd48fb30,0xbf7fb10f,
0x0,0xbf800000,0x3d48fb30,0xbf7fb10f,0x3dc8bd36,0xbf7ec46d,0x3e164083,0xbf7d3aac,0x3e47c5c2,0xbf7b14be,0x3e78cfcc,0xbf7853f8,
0x3e94a031,0xbf74fa0b,0x3eac7cd4,0xbf710908,0x3ec3ef15,0xbf6c835e,0x3edae880,0xbf676bd8,0x3ef15aea,0xbf61c598,0x3f039c3d,0xbf5b941a,
0x3f0e39da,0xbf54db31,0x3f187fc0,0xbf4d9f02,0x3f226799,0xbf45e403,0x3f2beb4a,0xbf3daef9,0x3f3504f3,0xbf3504f3,0x3f3daef9,0xbf2beb4a,
0x3f45e403,0xbf226799,0x3f4d9f02,0xbf187fc0,0x3f54db31,0xbf0e39da,0x3f5b941a,0xbf039c3d,0x3f61c598,0xbef15aea,0x3f676bd8,0xbedae880,
0x3f6c835e,0xbec3ef15,0x3f710908,0xbeac7cd4,0x3f74fa0b,0xbe94a031,0x3f7853f8,0xbe78cfcc,0x3f7b14be,0xbe47c5c2,0x3f7d3aac,0xbe164083,
0x3f7ec46d,0xbdc8bd36,0x3f7fb10f,0xbd48fb30,0x3f800000,0x0,0x3f7fffb1,0x3b490fc6,0x3f7ffec4,0x3bc90f88,0x3f7ffd39,0x3c16cb58,
0x3f7ffb11,0x3c490e90,0x3f7ff84a,0x3c7b514b,0x3f7ff4e6,0x3c96c9b6,0x3f7ff0e3,0x3cafea69,0x3f7fec43,0x3cc90ab0,0x3f7fe705,0x3ce22a7a,
0x3f7fe129,0x3cfb49ba,0x3f7fdaaf,0x3d0a342f,0x3f7fd397,0x3d16c32c,0x3f7fcbe2,0x3d2351cb,0x3f7fc38f,0x3d2fe007,0x3f7fba9e,0x3d3c6dd5,
0x3f7fb10f,0x3d48fb30,0x3f7fa6e3,0x3d55880e,0x3f7f9c18,0x3d621469,0x3f7f90b1,0x3d6ea038,0x3f7f84ab,0x3d7b2b74,0x3f7f7808,0x3d83db0a,
0x3f7f6ac7,0x3d8a200a,0x3f7f5ce9,0x3d9064b4,0x3f7f4e6d,0x3d96a905,0x3f7f3f54,0x3d9cecf9,0x3f7f2f9d,0x3da3308c,0x3f7f1f49,0x3da973ba,
0x3f7f0e58,0x3dafb680,0x3f7efcc9,0x3db5f8da,0x3f7eea9d,0x3dbc3ac3,0x3f7ed7d4,0x3dc27c39,0x3f7ec46d,0x3dc8bd36,0x3f7eb069,0x3dcefdb7,
0x3f7e9bc9,0x3dd53db9,0x3f7e868b,0x3ddb7d37,0x3f7e70b0,0x3de1bc2e,0x3f7e5a38,0x3de7fa9a,0x3f7e4323,0x3dee3876,0x3f7e2b72,0x3df475c0,
0x3f7e1324,0x3dfab273,0x3f7dfa38,0x3e007745,0x3f7de0b1,0x3e039502,0x3f7dc68c,0x3e06b26e,0x3f7dabcc,0x3e09cf86,0x3f7d906e,0x3e0cec4a,
0x3f7d7474,0x3e1008b7,0x3f7d57de,0x3e1324ca,0x3f7d3aac,0x3e164083,0x3f7d1cdd,0x3e195be0,0x3f7cfe73,0x3e1c76de,0x3f7cdf6c,0x3e1f917b,
0x3f7cbfc9,0x3e22abb6,0x3f7c9f8a,0x3e25c58c,0x3f7c7eb0,0x3e28defc,0x3f7c5d3a,0x3e2bf804,0x3f7c3b28,0x3e2f10a2,0x3f7c187a,0x3e3228d4,
0x3f7bf531,0x3e354098,0x3f7bd14d,0x3e3857ec,0x3f7baccd,0x3e3b6ecf,0x3f7b87b2,0x3e3e853e,0x3f7b61fc,0x3e419b37,0x3f7b3bab,0x3e44b0b9,
0x3f7b14be,0x3e47c5c2,0x3f7aed37,0x3e4ada4f,0x3f7ac516,0x3e4dee60,0x3f7a9c59,0x3e5101f1,0x3f7a7302,0x3e541501,0x3f7a4910,0x3e57278f,
0x3f7a1e84,0x3e5a3997,0x3f79f35e,0x3e5d4b1a,0x3f79c79d,0x3e605c13,0x3f799b43,0x3e636c83,0x3f796e4e,0x3e667c66,0x3f7940c0,0x3e698bba,
0x3f791298,0x3e6c9a7f,0x3f78e3d6,0x3e6fa8b2,0x3f78b47b,0x3e72b651,0x3f788486,0x3e75c35a,0x3f7853f8,0x3e78cfcc,0x3f7822d1,0x3e7bdba4,
0x3f77f110,0x3e7ee6e1,0x3f77beb7,0x3e80f8c0,0x3f778bc5,0x3e827dc0,0x3f77583a,0x3e840270,0x3f772417,0x3e8586ce,0x3f76ef5b,0x3e870ada,
0x3f76ba07,0x3e888e93,0x3f76841b,0x3e8a11f7,0x3f764d97,0x3e8b9507,0x3f76167a,0x3e8d17c0,0x3f75dec6,0x3e8e9a22,0x3f75a67b,0x3e901c2c,
0x3f756d97,0x3e919ddd,0x3f75341d,0x3e931f35,0x3f74fa0b,0x3e94a031,0x3f74bf62,0x3e9620d2,0x3f748422,0x3e97a117,0x3f74484b,0x3e9920fe,
0x3f740bdd,0x3e9aa086,0x3f73ced9,0x3e9c1faf,0x3f73913f,0x3e9d9e78,0x3f73530e,0x3e9f1cdf,0x3f731447,0x3ea09ae5,0x3f72d4eb,0x3ea21887,
0x3f7294f8,0x3ea395c5,0x3f725470,0x3ea5129f,0x3f721352,0x3ea68f12,0x3f71d19f,0x3ea80b1f,0x3f718f57,0x3ea986c4,0x3f714c7a,0x3eab0201,
0x3f710908,0x3eac7cd4,0x3f70c501,0x3eadf73c,0x3f708066,0x3eaf713a,0x3f703b37,0x3eb0eacb,0x3f6ff573,0x3eb263ef,0x3f6faf1b,0x3eb3dca5,
0x3f6f6830,0x3eb554ec,0x3f6f20b0,0x3eb6ccc3,0x3f6ed89e,0x3eb8442a,0x3f6e8ff8,0x3eb9bb1e,0x3f6e46be,0x3ebb31a0,0x3f6dfcf2,0x3ebca7af,
0x3f6db293,0x3ebe1d4a,0x3f6d67a1,0x3ebf926f,0x3f6d1c1d,0x3ec1071e,0x3f6cd007,0x3ec27b55,
};
__device__ const __align__(16) uint32_t TAB_TH[258] = {
0x3f800000,0x0,0x3f7ffb11,0x3c490e90,0x3f7fec43,0x3cc90ab0,0x3f7fd397,0x3d16c32c,0x3f7fb10f,0x3d48fb30,0x3f7f84ab,0x3d7b2b74,
0x3f7f4e6d,0x3d96a905,0x3f7f0e58,0x3dafb680,0x3f7ec46d,0x3dc8bd36,0x3f7e70b0,0x3de1bc2e,0x3f7e1324,0x3dfab273,0x3f7dabcc,0x3e09cf86,
0x3f7d3aac,0x3e164083,0x3f7cbfc9,0x3e22abb6,0x3f7c3b28,0x3e2f10a2,0x3f7baccd,0x3e3b6ecf,0x3f7b14be,0x3e47c5c2,0x3f7a7302,0x3e541501,
0x3f79c79d,0x3e605c13,0x3f791298,0x3e6c9a7f,0x3f7853f8,0x3e78cfcc,0x3f778bc5,0x3e827dc0,0x3f76ba07,0x3e888e93,0x3f75dec6,0x3e8e9a22,
0x3f74fa0b,0x3e94a031,0x3f740bdd,0x3e9aa086,0x3f731447,0x3ea09ae5,0x3f721352,0x3ea68f12,0x3f710908,0x3eac7cd4,0x3f6ff573,0x3eb263ef,
0x3f6ed89e,0x3eb8442a,0x3f6db293,0x3ebe1d4a,0x3f6c835e,0x3ec3ef15,0x3f6b4b0c,0x3ec9b953,0x3f6a09a7,0x3ecf7bca,0x3f68bf3c,0x3ed53641,
0x3f676bd8,0x3edae880,0x3f660f88,0x3ee0924f,0x3f64aa59,0x3ee63375,0x3f633c5a,0x3eebcbbb,0x3f61c598,0x3ef15aea,0x3f604621,0x3ef6e0cb,
0x3f5ebe05,0x3efc5d27,0x3f5d2d53,0x3f00e7e4,0x3f5b941a,0x3f039c3d,0x3f59f26a,0x3f064b82,0x3f584853,0x3f08f59b,0x3f5695e5,0x3f0b9a6b,
0x3f54db31,0x3f0e39da,0x3f531849,0x3f10d3cd,0x3f514d3d,0x3f13682a,0x3f4f7a1f,0x3f15f6d9,0x3f4d9f02,0x3f187fc0,0x3f4bbbf8,0x3f1b02c6,
0x3f49d112,0x3f1d7fd1,0x3f47de65,0x3f1ff6cb,0x3f45e403,0x3f226799,0x3f43e200,0x3f24d225,0x3f41d870,0x3f273656,0x3f3fc767,0x3f299415,
0x3f3daef9,0x3f2beb4a,0x3f3b8f3b,0x3f2e3bde,0x3f396842,0x3f3085bb,0x3f373a23,0x3f32c8c9,0x3f3504f3,0x3f3504f3,0x3f32c8c9,0x3f373a23,
0x3f3085bb,0x3f396842,0x3f2e3bde,0x3f3b8f3b,0x3f2beb4a,0x3f3daef9,0x3f299415,0x3f3fc767,0x3f273656,0x3f41d870,0x3f24d225,0x3f43e200,
0x3f226799,0x3f45e403,0x3f1ff6cb,0x3f47de65,0x3f1d7fd1,0x3f49d112,0x3f1b02c6,0x3f4bbbf8,0x3f187fc0,0x3f4d9f02,0x3f15f6d9,0x3f4f7a1f,
0x3f13682a,0x3f514d3d,0x3f10d3cd,0x3f531849,0x3f0e39da,0x3f54db31,0x3f0b9a6b,0x3f5695e5,0x3f08f59b,0x3f584853,0x3f064b82,0x3f59f26a,
0x3f039c3d,0x3f5b941a,0x3f00e7e4,0x3f5d2d53,0x3efc5d27,0x3f5ebe05,0x3ef6e0cb,0x3f604621,0x3ef15aea,0x3f61c598,0x3eebcbbb,0x3f633c5a,
0x3ee63375,0x3f64aa59,0x3ee0924f,0x3f660f88,0x3edae880,0x3f676bd8,0x3ed53641,0x3f68bf3c,0x3ecf7bca,0x3f6a09a7,0x3ec9b953,0x3f6b4b0c,
0x3ec3ef15,0x3f6c835e,0x3ebe1d4a,0x3f6db293,0x3eb8442a,0x3f6ed89e,0x3eb263ef,0x3f6ff573,0x3eac7cd4,0x3f710908,0x3ea68f12,0x3f721352,
0x3ea09ae5,0x3f731447,0x3e9aa086,0x3f740bdd,0x3e94a031,0x3f74fa0b,0x3e8e9a22,0x3f75dec6,0x3e888e93,0x3f76ba07,0x3e827dc0,0x3f778bc5,
0x3e78cfcc,0x3f7853f8,0x3e6c9a7f,0x3f791298,0x3e605c13,0x3f79c79d,0x3e541501,0x3f7a7302,0x3e47c5c2,0x3f7b14be,0x3e3b6ecf,0x3f7baccd,
0x3e2f10a2,0x3f7c3b28,0x3e22abb6,0x3f7cbfc9,0x3e164083,0x3f7d3aac,0x3e09cf86,0x3f7dabcc,0x3dfab273,0x3f7e1324,0x3de1bc2e,0x3f7e70b0,
0x3dc8bd36,0x3f7ec46d,0x3dafb680,0x3f7f0e58,0x3d96a905,0x3f7f4e6d,0x3d7b2b74,0x3f7f84ab,0x3d48fb30,0x3f7fb10f,0x3d16c32c,0x3f7fd397,
0x3cc90ab0,0x3f7fec43,0x3c490e90,0x3f7ffb11,0x0,0x3f800000,
};

__device__ __align__(1024) uint32_t g_z1[128 * 4096];
__device__ __align__(1024) uint32_t g_z2[128 * 4096];
__device__ __align__(1024) bf16 g_x1[S_ * D_];
__device__ __align__(1024) bf16 g_h[S_ * D_];
__device__ __align__(1024) bf16 g_u[F_ * D_];
__device__ __align__(1024) bf16 g_x2[S_ * D_];
__device__ __align__(1024) uint2 g_wt[129 * 2048];
__device__ __align__(1024) float4 g_wt0[2048];
__device__ float g_wmax[64];
__device__ __align__(128) unsigned int g_cnt[2][4][32];

#define TL(kid, pt)
#define TLARG
#define TLPASS(k)

__device__ __forceinline__ uint32_t smem_u32(const void* p) { return (uint32_t)__cvta_generic_to_shared(p); }
__device__ __forceinline__ void griddep_wait() { asm volatile("griddepcontrol.wait;" ::: "memory"); }
__device__ __forceinline__ void griddep_launch() { asm volatile("griddepcontrol.launch_dependents;" ::: "memory"); }

__device__ __forceinline__ uint32_t pack_h2(float lo, float hi) {
    uint32_t r; asm("cvt.rn.f16x2.f32 %0, %1, %2;" : "=r"(r) : "f"(hi), "f"(lo)); return r;
}
__device__ __forceinline__ uint32_t pack_bf2(float lo, float hi) {
    uint32_t r; asm("cvt.rn.bf16x2.f32 %0, %1, %2;" : "=r"(r) : "f"(hi), "f"(lo)); return r;
}
__device__ __forceinline__ float bf_lo(uint32_t w) { return __uint_as_float(w << 16); }
__device__ __forceinline__ float bf_hi(uint32_t w) { return __uint_as_float(w & 0xffff0000u); }
__device__ __forceinline__ float bf16r(float x) { return __uint_as_float(pack_bf2(0.f, x) & 0xffff0000u); }

__device__ __forceinline__ void mma16816(float (&d)[4], const uint32_t (&a)[4], uint32_t b0, uint32_t b1) {
    asm("mma.sync.aligned.m16n8k16.row.col.f32.f16.f16.f32 {%0,%1,%2,%3}, {%4,%5,%6,%7}, {%8,%9}, {%0,%1,%2,%3};"
        : "+f"(d[0]), "+f"(d[1]), "+f"(d[2]), "+f"(d[3])
        : "r"(a[0]), "r"(a[1]), "r"(a[2]), "r"(a[3]), "r"(b0), "r"(b1));
}

__device__ __forceinline__ void mma16816z(float (&d)[4], const uint32_t (&a)[4], uint32_t b0, uint32_t b1) {
    asm("mma.sync.aligned.m16n8k16.row.col.f32.f16.f16.f32 {%0,%1,%2,%3}, {%4,%5,%6,%7}, {%8,%9}, {%10,%10,%10,%10};"
        : "=f"(d[0]), "=f"(d[1]), "=f"(d[2]), "=f"(d[3])
        : "r"(a[0]), "r"(a[1]), "r"(a[2]), "r"(a[3]), "r"(b0), "r"(b1), "f"(0.f));
}
__device__ __forceinline__ void mma_stat(float (&d)[4], uint32_t x0, uint32_t x1) {
    asm("mma.sync.aligned.m16n8k16.row.col.f32.bf16.bf16.f32 {%0,%1,%2,%3}, {%4,%6,%5,%6}, {%4,%5}, {%0,%1,%2,%3};"
        : "+f"(d[0]), "+f"(d[1]), "+f"(d[2]), "+f"(d[3])
        : "r"(x0), "r"(x1), "r"(0x3f803f80u));
}
__device__ __forceinline__ uint32_t bf2_sub(uint32_t a, uint32_t b) {
    uint32_t r; asm("sub.rn.bf16x2 %0, %1, %2;" : "=r"(r) : "r"(a), "r"(b)); return r;
}
__device__ __forceinline__ uint32_t bf2_add(uint32_t a, uint32_t b) {
    uint32_t r; asm("add.rn.bf16x2 %0, %1, %2;" : "=r"(r) : "r"(a), "r"(b)); return r;
}
__device__ __forceinline__ uint32_t bf2_mul(uint32_t a, uint32_t b) {
    uint32_t r; asm("mul.rn.bf16x2 %0, %1, %2;" : "=r"(r) : "r"(a), "r"(b)); return r;
}
__device__ __forceinline__ uint32_t bf2_fma(uint32_t a, uint32_t b, uint32_t c) {
    uint32_t r; asm("fma.rn.bf16x2 %0, %1, %2, %3;" : "=r"(r) : "r"(a), "r"(b), "r"(c)); return r;
}

__device__ __forceinline__ void mbar_init(uint32_t bar, int cnt) {
    asm volatile("mbarrier.init.shared::cta.b64 [%0], %1;" ::"r"(bar), "r"(cnt) : "memory");
}
__device__ __forceinline__ void mbar_expect_tx(uint32_t bar, uint32_t bytes) {
    asm volatile("mbarrier.arrive.expect_tx.shared::cta.b64 _, [%0], %1;" ::"r"(bar), "r"(bytes) : "memory");
}
__device__ __forceinline__ void mbar_wait(uint32_t bar, uint32_t parity) {
    asm volatile(
        "{\n.reg .pred p;\n"
        "WL_%=:\n"
        "mbarrier.try_wait.parity.shared::cta.b64 p, [%0], %1;\n"
        "@p bra WD_%=;\n"
        "bra WL_%=;\n"
        "WD_%=:\n}" ::"r"(bar), "r"(parity) : "memory");
}
__device__ __forceinline__ void bulk_load(uint32_t dst, const void* src, uint32_t bytes, uint32_t bar) {
    asm volatile("cp.async.bulk.shared::cluster.global.mbarrier::complete_tx::bytes [%0], [%1], %2, [%3];"
                 ::"r"(dst), "l"(src), "r"(bytes), "r"(bar) : "memory");
}
__device__ __forceinline__ void l2_prefetch(const void* src, uint32_t bytes) {
    asm volatile("cp.async.bulk.prefetch.L2.global [%0], %1;" ::"l"(src), "r"(bytes) : "memory");
}

struct GlobTab {
    const uint4* p;
    __device__ __forceinline__ void u(uint32_t (&d)[4], int i) const { uint4 q = __ldg(p + 32 * i); d[0] = q.x; d[1] = q.y; d[2] = q.z; d[3] = q.w; }
};
struct SmemTab {
    const uint4* p;
    __device__ __forceinline__ void u(uint32_t (&d)[4], int i) const { uint4 q = p[32 * i]; d[0] = q.x; d[1] = q.y; d[2] = q.z; d[3] = q.w; }
    __device__ __forceinline__ void f(float (&d)[4], int i) const {
        uint4 q = p[32 * i];
        d[0] = __uint_as_float(q.x); d[1] = __uint_as_float(q.y); d[2] = __uint_as_float(q.z); d[3] = __uint_as_float(q.w);
    }
};

struct FftConst {
    uint32_t Are[2][4], Aim[2][4], Fc[4], Fs[4], Fn[4];
    float twc[2][4], tws[2][4];
    __device__ __forceinline__ void load(const uint32_t* tab, int lane) {
        const uint4* p = (const uint4*)tab + lane;
        uint4 q;
#define LD4(dst, i) q = __ldg(p + 32 * (i)); dst[0] = q.x; dst[1] = q.y; dst[2] = q.z; dst[3] = q.w;
#define LD4F(dst, i) q = __ldg(p + 32 * (i)); dst[0] = __uint_as_float(q.x); dst[1] = __uint_as_float(q.y); dst[2] = __uint_as_float(q.z); dst[3] = __uint_as_float(q.w);
        LD4(Are[0], 0) LD4(Are[1], 1) LD4(Aim[0], 2) LD4(Aim[1], 3) LD4(Fc, 4) LD4(Fs, 5) LD4(Fn, 6)
        LD4F(twc[0], 7) LD4F(twc[1], 8) LD4F(tws[0], 9) LD4F(tws[1], 10)
    }
};

__device__ __forceinline__ void stage_inter(const uint32_t (&Are)[2][4], const uint32_t (&Aim)[2][4],
                                            const uint32_t (&B)[4][2],
                                            float (&Cre)[2][4], float (&Cim)[2][4]) {
#pragma unroll
    for (int jn = 0; jn < 2; jn++) {
        mma16816z(Cre[jn], Are[0], B[0][jn], B[1][jn]);
        mma16816z(Cim[jn], Aim[0], B[0][jn], B[1][jn]);
        mma16816(Cre[jn], Are[1], B[2][jn], B[3][jn]);
        mma16816(Cim[jn], Aim[1], B[2][jn], B[3][jn]);
    }
}
__device__ __forceinline__ void stage_c2b(const uint32_t (&Fc)[4], const uint32_t (&F1)[4], const uint32_t (&F2)[4],
                                          const float (&Cre)[2][4], const float (&Cim)[2][4],
                                          float (&Ore)[2][4], float (&Oim)[2][4]) {
#pragma unroll
    for (int j = 0; j < 2; j++) {
        uint32_t r0 = pack_h2(Cre[0][2 * j], Cre[0][2 * j + 1]), r1 = pack_h2(Cre[1][2 * j], Cre[1][2 * j + 1]);
        uint32_t i0 = pack_h2(Cim[0][2 * j], Cim[0][2 * j + 1]), i1 = pack_h2(Cim[1][2 * j], Cim[1][2 * j + 1]);
        mma16816z(Ore[j], Fc, r0, r1);
        mma16816z(Oim[j], Fc, i0, i1);
        mma16816(Ore[j], F1, i0, i1);
        mma16816(Oim[j], F2, r0, r1);
    }
}
__device__ __forceinline__ void stage_c2a(const uint32_t (&Fc)[4], const uint32_t (&F1)[4], const uint32_t (&F2)[4],
                                          const float (&Cre)[2][4], const float (&Cim)[2][4],
                                          float (&Ore)[2][4], float (&Oim)[2][4]) {
    uint32_t ar[4], ai[4];
    ar[0] = pack_h2(Cre[0][0], Cre[0][1]); ar[1] = pack_h2(Cre[0][2], Cre[0][3]);
    ar[2] = pack_h2(Cre[1][0], Cre[1][1]); ar[3] = pack_h2(Cre[1][2], Cre[1][3]);
    ai[0] = pack_h2(Cim[0][0], Cim[0][1]); ai[1] = pack_h2(Cim[0][2], Cim[0][3]);
    ai[2] = pack_h2(Cim[1][0], Cim[1][1]); ai[3] = pack_h2(Cim[1][2], Cim[1][3]);
#pragma unroll
    for (int j = 0; j < 2; j++) {
        mma16816z(Ore[j], ar, Fc[j], Fc[j + 2]);
        mma16816z(Oim[j], ai, Fc[j], Fc[j + 2]);
        mma16816(Ore[j], ai, F1[j], F1[j + 2]);
        mma16816(Oim[j], ar, F2[j], F2[j + 2]);
    }
}
template <bool INV>
__device__ __forceinline__ void twiddle(float (&Cre)[2][4], float (&Cim)[2][4], const float (&twc)[2][4], const float (&tws)[2][4]) {
#pragma unroll
    for (int jn = 0; jn < 2; jn++)
#pragma unroll
        for (int q = 0; q < 4; q++) {
            float re = Cre[jn][q], im = Cim[jn][q];
            if (!INV) {
                Cre[jn][q] = re * twc[jn][q] + im * tws[jn][q];
                Cim[jn][q] = im * twc[jn][q] - re * tws[jn][q];
            } else {
                Cre[jn][q] = re * twc[jn][q] - im * tws[jn][q];
                Cim[jn][q] = im * twc[jn][q] + re * tws[jn][q];
            }
        }
}

__device__ __forceinline__ void warp_ln(uint32_t (&v)[8], int lane) {
    const int g = lane >> 2;
    float d[4] = {0.f, 0.f, 0.f, 0.f}, e[4] = {0.f, 0.f, 0.f, 0.f};
    mma_stat(d, v[0], v[1]);
    mma_stat(e, v[2], v[3]);
    mma_stat(d, v[4], v[5]);
    mma_stat(e, v[6], v[7]);
    float s1 = (d[2] + d[3]) + (e[2] + e[3]);
    float s2 = (g & 1) ? d[1] + e[1] : d[0] + e[0];
    s2 = __shfl_sync(0xffffffffu, s2, 4 * g + (g >> 1));
    s1 += __shfl_xor_sync(0xffffffffu, s1, 1);
    s2 += __shfl_xor_sync(0xffffffffu, s2, 4);
    s1 += __shfl_xor_sync(0xffffffffu, s1, 2);
    s2 += __shfl_xor_sync(0xffffffffu, s2, 8);
    s2 += __shfl_xor_sync(0xffffffffu, s2, 16);
    float mean = s1 * (1.f / 512.f);
    float var = fmaxf(fmaf(-mean, mean, s2 * (1.f / 512.f)), 0.f);
    float sq, rd;
    asm("sqrt.approx.f32 %0, %1;" : "=f"(sq) : "f"(bf16r(bf16r(var) + 1e-5f)));
    float den = bf16r(sq);
    asm("rcp.approx.f32 %0, %1;" : "=f"(rd) : "f"(den));
    float rh = bf16r(rd);
    const uint32_t m2 = pack_bf2(mean, mean), rh2 = pack_bf2(rh, rh), rl2 = pack_bf2(rd - rh, rd - rh);
#pragma unroll
    for (int i = 0; i < 8; i++) {
        uint32_t dd = bf2_sub(v[i], m2);
        v[i] = bf2_fma(dd, rh2, bf2_mul(dd, rl2));
    }
}

__device__ __forceinline__ float wscale_exp(float m, float& inv) {
#pragma unroll
    for (int o = 16; o > 0; o >>= 1) m = fmaxf(m, __shfl_xor_sync(0xffffffffu, m, o));
    int e = (int)((__float_as_uint(m) >> 23) & 0xff);
    e = min(max(e, 2), 250);
    inv = __uint_as_float((uint32_t)(e + 1) << 23);
    return __uint_as_float((uint32_t)(253 - e) << 23);
}

constexpr int WP_CH = 32 * 514;
constexpr int WP_ARR = 2 * WP_CH + 528;
constexpr int WP_SMEM = 2 * WP_ARR + 64;
__device__ __forceinline__ void wprep(const bf16* __restrict__ wr, const bf16* __restrict__ wi, int q, uint8_t* wsm TLARG) {
    __shared__ __align__(8) uint64_t bar;
    __shared__ float smx[16];
    const int tid = threadIdx.x, lane = tid & 31, w = tid >> 5;
    if (tid == 0) {
        mbar_init(smem_u32(&bar), 1);
        asm volatile("fence.mbarrier_init.release.cluster;" ::: "memory");
        mbar_expect_tx(smem_u32(&bar), 2 * WP_ARR);
        const uint8_t* src[2] = {(const uint8_t*)wr, (const uint8_t*)wi};
#pragma unroll
        for (int a = 0; a < 2; a++) {
            uint32_t d = smem_u32(wsm) + a * WP_ARR;
            bulk_load(d, src[a] + (size_t)q * WP_CH, WP_CH, smem_u32(&bar));
            bulk_load(d + WP_CH, src[a] + (size_t)(63 - q) * WP_CH, WP_CH, smem_u32(&bar));
            bulk_load(d + 2 * WP_CH, src[a] + (size_t)((64 - q) & 63) * WP_CH, 528, smem_u32(&bar));
        }
    }
    __syncthreads();
    mbar_wait(smem_u32(&bar), 0);
    TL(kid, 8);
    const int c = lane >> 2, row = c + 8 * (lane & 3);
    const uint16_t* Ar = (const uint16_t*)(wsm) + row * 257;
    const uint16_t* Ai = (const uint16_t*)(wsm + WP_ARR) + row * 257;
    const uint16_t* Br = (const uint16_t*)(wsm + WP_CH) + (32 - row) * 257;
    const uint16_t* Bi = (const uint16_t*)(wsm + WP_ARR + WP_CH) + (32 - row) * 257;
    const int e1 = q >> 2, t = e1 >> 2, p = 2 * (e1 & 1) + ((e1 >> 1) & 1);
    const int g = 2 * (q & 3) + ((lane >> 1) & 1), h = lane & 1;
    const int off = ((p * 8 + c) * 32 + t * 8 + g) * 2 + h;
    float mx = 0.f;
    uint32_t va[9], vb[9];
#pragma unroll
    for (int i = 0; i < 9; i++) {
        const int j = min(w + 16 * i, 128);
        va[i] = (uint32_t)Ar[j] | ((uint32_t)Ai[j] << 16);
        vb[i] = (uint32_t)Br[256 - j] | ((uint32_t)Bi[256 - j] << 16);
    }
    uint32_t mxa = 0;
#pragma unroll
    for (int i = 0; i < 9; i++) {
        const int j = w + 16 * i;
        mxa = __vmaxu2(mxa, __vmaxu2(va[i] & 0x7fff7fffu, vb[i] & 0x7fff7fffu));
        if (j <= 128) g_wt[j * 2048 + off] = make_uint2(va[i], vb[i] ^ 0x80000000u);
    }
    mx = fmaxf(bf_lo(mxa), bf_hi(mxa));
    if (w == 0) {
        float a_re = 0.5f * (bf_lo(Ar[0]) + bf_lo(Br[0])), a_im = 0.5f * (bf_lo(Ai[0]) - bf_lo(Bi[0]));
        float b_re = 0.5f * (bf_lo(Ar[256]) + bf_lo(Br[256])), b_im = 0.5f * (bf_lo(Ai[256]) - bf_lo(Bi[256]));
        g_wt0[off] = make_float4(a_re, a_im, b_re, b_im);
    }
#pragma unroll
    for (int o = 16; o > 0; o >>= 1) mx = fmaxf(mx, __shfl_xor_sync(0xffffffffu, mx, o));
    if (lane == 0) smx[w] = mx;
    __syncthreads();
    if (tid == 0) {
        float m = smx[0];
#pragma unroll
        for (int i = 1; i < 16; i++) m = fmaxf(m, smx[i]);
        g_wmax[q] = m;
    }
}

constexpr int P1_SMEM = 16384;
__global__ void __maxnreg__(56) k_p1(const bf16* __restrict__ x, const bf16* __restrict__ wr, const bf16* __restrict__ wi TLARG) {
    extern __shared__ __align__(128) uint8_t dsm[];
    uint32_t* stage = (uint32_t*)dsm;
    uint4* tab = (uint4*)dsm;
    TL(kid, 0);
    griddep_launch();
    if (blockIdx.x >= 128) {
        wprep(wr, wi, blockIdx.x - 128, dsm TLPASS(kid));
        TL(kid, 5);
        return;
    }
    const int lane = threadIdx.x & 31, w = threadIdx.x >> 5, g = lane >> 2, t = lane & 3;
    const uint2* row = (const uint2*)(x + (size_t)(blockIdx.x * 16 + w) * 512);
    uint4 tv = make_uint4(0, 0, 0, 0);
    if (threadIdx.x < 352) tv = __ldg((const uint4*)TAB_P1 + threadIdx.x);
    const SmemTab T{tab + lane};
    griddep_wait();
    TL(kid, 1);
    uint32_t v[8];
#pragma unroll
    for (int i = 0; i < 4; i++) {
        uint2 r = __ldcg(row + 8 * (t + 4 * i) + g);
        v[2 * i] = r.x; v[2 * i + 1] = r.y;
    }
    if (threadIdx.x < 352) tab[threadIdx.x] = tv;
    __syncthreads();
    warp_ln(v, lane);
    TL(kid, 3);
    uint32_t B[4][2];
#pragma unroll
    for (int i = 0; i < 4; i++) {
        B[i][0] = pack_h2(bf_lo(v[2 * i]), bf_hi(v[2 * i]));
        B[i][1] = pack_h2(bf_lo(v[2 * i + 1]), bf_hi(v[2 * i + 1]));
    }
    float Cre[2][4], Cim[2][4], Ore[2][4], Oim[2][4];
    {
        uint32_t Are[2][4], Aim[2][4];
        T.u(Are[0], 0); T.u(Are[1], 1); T.u(Aim[0], 2); T.u(Aim[1], 3);
        stage_inter(Are, Aim, B, Cre, Cim);
    }
    {
        float twc[2][4], tws[2][4];
        T.f(twc[0], 7); T.f(twc[1], 8); T.f(tws[0], 9); T.f(tws[1], 10);
        twiddle<false>(Cre, Cim, twc, tws);
    }
    {
        uint32_t Fc[4], Fs[4], Fn[4];
        T.u(Fc, 4); T.u(Fs, 5); T.u(Fn, 6);
        stage_c2b(Fc, Fs, Fn, Cre, Cim, Ore, Oim);
    }
    const int f = (t >> 1) | ((g & 3) << 1);
    const int pos = 2 * ((w >> 1) ^ f) + (w & 1);
    __syncthreads();
#pragma unroll
    for (int j = 0; j < 2; j++)
#pragma unroll
        for (int q = 0; q < 4; q++) {
            int k = (t + 4 * (q & 1) + 8 * j) + 16 * (g + 8 * (q >> 1));
            stage[k * 16 + pos] = pack_h2(Ore[j][q], Oim[j][q]);
        }
    TL(kid, 4);
    __syncthreads();
    uint4* dst = (uint4*)g_z1 + (size_t)(threadIdx.x >> 2) * 512 + blockIdx.x * 4 + (threadIdx.x & 3);
#pragma unroll
    for (int i = 0; i < 2; i++) dst[(size_t)i * 128 * 512] = ((const uint4*)stage)[threadIdx.x + 512 * i];
    TL(kid, 2);
}

__device__ __forceinline__ int swz_f(int k) { return ((k >> 1) & 1) | (((k >> 4) & 3) << 1); }

template <bool WEARLY>
__global__ void __maxnreg__(144) k_p2(const uint8_t* __restrict__ pf, int pf_bytes TLARG) {
    __shared__ __align__(16) uint32_t XB[2 * 8 * 416];
    __shared__ __align__(16) uint32_t ZB[2 * 8 * 264];
    __shared__ __align__(8) uint64_t bar;
    TL(kid, 0);
    if (threadIdx.x == 0) {
        mbar_init(smem_u32(&bar), 1);
        asm volatile("fence.mbarrier_init.release.cluster;" ::: "memory");
        mbar_expect_tx(smem_u32(&bar), 16384);
        if (pf_bytes && blockIdx.x < 128) l2_prefetch(pf + (size_t)blockIdx.x * pf_bytes, pf_bytes);
    }
    __syncthreads();
    const int lane = threadIdx.x & 31, w = threadIdx.x >> 5, g = lane >> 2, t = lane & 3;
    const int j = blockIdx.x;
    if (j > 128) {
        griddep_wait();
        griddep_launch();
        const long long t0 = clock64();
        while (clock64() - t0 < 4000) __nanosleep(100);
        return;
    }
    const int kc[2] = {j, (256 - j) & 255};
    const int fc[2] = {swz_f(kc[0]), swz_f(kc[1])};
    FftConst K;
    K.load(TAB_P2, lane);
    uint32_t M8[2][4], M8i[2][4];
    float tac[2][4], tas[2][4], tbc[2][4], tbs[2][4];
    {
        const uint4* p = (const uint4*)TAB_P2 + lane;
        uint4 q;
        LD4(M8[0], 11) LD4(M8[1], 12) LD4(M8i[0], 13) LD4(M8i[1], 14)
    }
    {
        const float2* T128 = (const float2*)TAB_TW;
        const float2* T2k = T128 + 128;
#pragma unroll
        for (int a = 0; a < 2; a++) {
            const float2 fa = __ldg(T128 + (((2 * w + a) * g) & 127)), ia = __ldg(T128 + (((2 * g + a) * w) & 127));
#pragma unroll
            for (int q = 0; q < 4; q++) {
                const float2 fb = __ldg(T2k + (4 * t + q) * g), ib = __ldg(T2k + (4 * t + q) * w);
                tac[a][q] = fa.x * fb.x - fa.y * fb.y; tas[a][q] = fa.x * fb.y + fa.y * fb.x;
                tbc[a][q] = ia.x * ib.x - ia.y * ib.y; tbs[a][q] = ia.x * ib.y + ia.y * ib.x;
            }
        }
    }
    const float cth = __uint_as_float(TAB_TH[2 * j]), sth = __uint_as_float(TAB_TH[2 * j + 1]);
    uint4 wq[8];
    const int wpos = w * 32 + t * 8 + g;
    float winv, hs;
    uint2 zin[2][2][2];
    if (!WEARLY) {
        griddep_wait();
        griddep_launch();
        TL(kid, 1);
        if (lane == 0) {
#pragma unroll
            for (int a = 0; a < 2; a++)
                bulk_load(smem_u32(&ZB[(a * 8 + w) * 264]), g_z1 + (size_t)kc[a] * 2048 + w * 256, 1024, smem_u32(&bar));
        }
    }
    if (j == 0) {
#pragma unroll
        for (int p = 0; p < 4; p++) {
            wq[2 * p] = __ldcg((const uint4*)&g_wt0[(p * 256 + wpos) * 2]);
            wq[2 * p + 1] = __ldcg((const uint4*)&g_wt0[(p * 256 + wpos) * 2 + 1]);
        }
    } else {
#pragma unroll
        for (int p = 0; p < 4; p++) wq[p] = __ldcg((const uint4*)&g_wt[(size_t)j * 2048 + (p * 256 + wpos) * 2]);
    }
    float wm = fmaxf(__ldcg(&g_wmax[lane]), __ldcg(&g_wmax[lane + 32]));
    if (WEARLY) {
        griddep_wait();
        griddep_launch();
        TL(kid, 1);
        if (lane == 0) {
#pragma unroll
            for (int a = 0; a < 2; a++)
                bulk_load(smem_u32(&ZB[(a * 8 + w) * 264]), g_z1 + (size_t)kc[a] * 2048 + w * 256, 1024, smem_u32(&bar));
        }
    }

    if (WEARLY) hs = 0.5f * wscale_exp(wm, winv);
    TL(kid, 10);
    mbar_wait(smem_u32(&bar), 0);
    TL(kid, 11);
#pragma unroll
    for (int col = 0; col < 2; col++)
#pragma unroll
        for (int be = 0; be < 2; be++)
#pragma unroll
            for (int ar = 0; ar < 2; ar++)
                zin[col][be][ar] = *(const uint2*)&ZB[(col * 8 + t + 4 * ar) * 264 + (2 * w + be) * 16 + 2 * (g ^ fc[col])];

#pragma unroll
    for (int col = 0; col < 2; col++)
#pragma unroll
        for (int be = 0; be < 2; be++) {
            float C0[4], C1[4];
            mma16816z(C0, M8[col], zin[col][be][0].x, zin[col][be][1].x);
            mma16816z(C1, M8[col], zin[col][be][0].y, zin[col][be][1].y);
            uint32_t o[4];
#pragma unroll
            for (int i = 0; i < 4; i++) {
                float re = (i & 1) ? C1[i >> 1] : C0[i >> 1];
                float im = (i & 1) ? C1[2 + (i >> 1)] : C0[2 + (i >> 1)];
                o[i] = pack_h2(re * tac[be][i] + im * tas[be][i], im * tac[be][i] - re * tas[be][i]);
            }
            *(uint4*)&XB[col * 3328 + g * 416 + 16 * (g & 1) + (2 * w + be) * 24 + 4 * t] = make_uint4(o[0], o[1], o[2], o[3]);
        }
    TL(kid, 3);
    __syncthreads();
    if (!WEARLY) hs = 0.5f * wscale_exp(wm, winv);

    float Ure[2][2][4], Uim[2][2][4];
#pragma unroll
    for (int col = 0; col < 2; col++) {
        uint32_t B[4][2];
#pragma unroll
        for (int i = 0; i < 4; i++) {
            uint2 q2 = *(const uint2*)&XB[col * 3328 + w * 416 + 16 * (w & 1) + (t + 4 * i) * 24 + 2 * g];
            B[i][0] = q2.x; B[i][1] = q2.y;
        }
        float Cre[2][4], Cim[2][4];
        stage_inter(K.Are, K.Aim, B, Cre, Cim);
        twiddle<false>(Cre, Cim, K.twc, K.tws);
        stage_c2a(K.Fc, K.Fs, K.Fn, Cre, Cim, Ure[col], Uim[col]);
    }
#pragma unroll
    for (int jp = 0; jp < 2; jp++)
#pragma unroll
        for (int q = 0; q < 4; q++) {
            const int p = 2 * jp + (q & 1), h = q >> 1;
            float p0, p1, p2, p3;
            if (j == 0) {
                const uint4 z = wq[2 * p + h];
                p0 = __uint_as_float(z.x); p1 = __uint_as_float(z.y); p2 = __uint_as_float(z.z); p3 = __uint_as_float(z.w);
            } else {
                const uint32_t a = h ? wq[p].z : wq[p].x, b = h ? wq[p].w : wq[p].y;
                p0 = bf_lo(a); p1 = bf_hi(a); p2 = bf_lo(b); p3 = bf_hi(b);
            }
            float sr = (p0 + p2) * hs, si = (p1 + p3) * hs;
            float dr = (p0 - p2) * hs, di = (p1 - p3) * hs;
            float a1r = sr - sth * dr, a1i = si - sth * di;
            float a2r = sr + sth * dr, a2i = si + sth * di;
            float br = -cth * di, bi = cth * dr;
            float ur = Ure[0][jp][q], ui = Uim[0][jp][q], vr = Ure[1][jp][q], vi = Uim[1][jp][q];
            Ure[0][jp][q] = a1r * ur - a1i * ui + br * vr - bi * vi;
            Uim[0][jp][q] = a1r * ui + a1i * ur + br * vi + bi * vr;
            Ure[1][jp][q] = a2r * vr - a2i * vi - br * ur + bi * ui;
            Uim[1][jp][q] = a2r * vi + a2i * vr - br * ui - bi * ur;
        }
    TL(kid, 4);
#pragma unroll
    for (int col = 0; col < 2; col++) {
        float Cre[2][4], Cim[2][4], Ore[2][4], Oim[2][4];
        stage_c2b(K.Fc, K.Fn, K.Fs, Ure[col], Uim[col], Cre, Cim);
        twiddle<true>(Cre, Cim, K.twc, K.tws);
        stage_c2b(K.Fc, K.Fn, K.Fs, Cre, Cim, Ore, Oim);
#pragma unroll
        for (int h = 0; h < 2; h++) {
            uint32_t o[4];
#pragma unroll
            for (int i = 0; i < 4; i++) {
                float re = Ore[i & 1][2 * h + (i >> 1)], im = Oim[i & 1][2 * h + (i >> 1)];
                o[i] = pack_h2(re * tbc[h][i] - im * tbs[h][i], im * tbc[h][i] + re * tbs[h][i]);
            }
            *(uint4*)&XB[col * 3328 + w * 416 + 8 * (w & 3) + (2 * g + h) * 24 + 4 * t] = make_uint4(o[0], o[1], o[2], o[3]);
        }
    }
    TL(kid, 5);
    __syncthreads();
#pragma unroll
    for (int col = 0; col < 2; col++) {
        if (col == 1 && kc[0] == kc[1]) break;
#pragma unroll
        for (int be = 0; be < 2; be++) {
            uint2 q0 = *(const uint2*)&XB[col * 3328 + t * 416 + 8 * t + (2 * w + be) * 24 + 2 * g];
            uint2 q1 = *(const uint2*)&XB[col * 3328 + (t + 4) * 416 + 8 * t + (2 * w + be) * 24 + 2 * g];
            float C0[4], C1[4];
            mma16816z(C0, M8i[col], q0.x, q1.x);
            mma16816z(C1, M8i[col], q0.y, q1.y);
            uint32_t o0 = pack_h2(C0[0], C0[2]), o1 = pack_h2(C1[0], C1[2]);
            uint32_t o2 = pack_h2(C0[1], C0[3]), o3 = pack_h2(C1[1], C1[3]);
            uint4 ov = (fc[col] & 1) ? make_uint4(o2, o3, o0, o1) : make_uint4(o0, o1, o2, o3);
            int sblk = 16 * g + 2 * w + be;
            *(uint4*)&g_z2[(size_t)sblk * 4096 + kc[col] * 16 + 4 * (t ^ (fc[col] >> 1))] = ov;
        }
    }
    TL(kid, 2);
}

__global__ void __maxnreg__(56) k_p3(const bf16* __restrict__ x, unsigned int* __restrict__ cnt,
                                     const uint8_t* __restrict__ pf, int pf_bytes TLARG) {
    __shared__ __align__(128) uint32_t buf[4096];
    __shared__ __align__(8) uint64_t bar;
    TL(kid, 0);
    griddep_launch();
    const int lane = threadIdx.x & 31, w = threadIdx.x >> 5, g = lane >> 2, t = lane & 3;
    if (threadIdx.x == 0) {
        mbar_init(smem_u32(&bar), 1);
        asm volatile("fence.mbarrier_init.release.cluster;" ::: "memory");
        if (pf_bytes) l2_prefetch(pf + (size_t)blockIdx.x * pf_bytes, pf_bytes);
    }
    uint4 park = make_uint4(0, 0, 0, 0);
    if (threadIdx.x < 224) park = __ldg((const uint4*)TAB_P3 + 128 + threadIdx.x);
    uint32_t Are[2][4], Aim[2][4];
    {
        const GlobTab G{(const uint4*)TAB_P3 + lane};
        G.u(Are[0], 0); G.u(Are[1], 1); G.u(Aim[0], 2); G.u(Aim[1], 3);
    }
    const SmemTab T{(const uint4*)buf + lane - 128};
    const size_t row0 = (size_t)(blockIdx.x * 16 + w) * 512;
    uint4 xr[2];
#pragma unroll
    for (int h = 0; h < 2; h++) xr[h] = __ldcg((const uint4*)(x + row0) + 4 * (g + 8 * h) + t);
    float winv;
    wscale_exp(fmaxf(__ldcg(&g_wmax[lane]), __ldcg(&g_wmax[lane + 32])), winv);
    __syncthreads();
    griddep_wait();
    TL(kid, 1);
    if (threadIdx.x == 0) {
        mbar_expect_tx(smem_u32(&bar), 16384);
        bulk_load(smem_u32(buf), g_z2 + (size_t)blockIdx.x * 4096, 16384, smem_u32(&bar));
    }
    if (blockIdx.x == 0 && threadIdx.x >= 384) cnt[threadIdx.x - 384] = 0;
    const int f = ((g >> 1) & 1) | (t << 1);
    const int pos = 2 * ((w >> 1) ^ f) + (w & 1);
    mbar_wait(smem_u32(&bar), 0);
    TL(kid, 3);
    uint32_t B[4][2];
#pragma unroll
    for (int i = 0; i < 4; i++)
#pragma unroll
        for (int jn = 0; jn < 2; jn++) B[i][jn] = buf[(16 * (t + 4 * i) + g + 8 * jn) * 16 + pos];
    __syncthreads();
    if (threadIdx.x < 224) ((uint4*)buf)[threadIdx.x] = park;
    float Cre[2][4], Cim[2][4], Ore[2][4], Oim[2][4];
    stage_inter(Are, Aim, B, Cre, Cim);
    __syncthreads();
    {
        float twc[2][4], tws[2][4];
        T.f(twc[0], 7); T.f(twc[1], 8); T.f(tws[0], 9); T.f(tws[1], 10);
        twiddle<true>(Cre, Cim, twc, tws);
    }
    {
        uint32_t Fc[4], Fs[4], Fn[4];
        T.u(Fc, 4); T.u(Fs, 5); T.u(Fn, 6);
        stage_c2b(Fc, Fn, Fs, Cre, Cim, Ore, Oim);
    }
    uint32_t v[8];
#pragma unroll
    for (int h = 0; h < 2; h++) {
        const uint32_t xw[4] = {xr[h].x, xr[h].y, xr[h].z, xr[h].w};
#pragma unroll
        for (int i = 0; i < 4; i++)
            v[4 * h + i] = bf2_add(xw[i], pack_bf2(Ore[i & 1][2 * h + (i >> 1)] * winv, Oim[i & 1][2 * h + (i >> 1)] * winv));
        ((uint4*)(g_x1 + row0))[4 * (g + 8 * h) + t] = make_uint4(v[4 * h], v[4 * h + 1], v[4 * h + 2], v[4 * h + 3]);
    }
    TL(kid, 4);
    warp_ln(v, lane);
    warp_ln(v, lane);
    TL(kid, 5);
#pragma unroll
    for (int h = 0; h < 2; h++)
        ((uint4*)(g_h + row0))[4 * (g + 8 * h) + t] = make_uint4(v[4 * h], v[4 * h + 1], v[4 * h + 2], v[4 * h + 3]);
    TL(kid, 2);
}

__device__ __forceinline__ uint64_t make_desc(uint32_t addr, uint32_t lbo, uint32_t sbo) {
    return (uint64_t)((addr & 0x3FFFF) >> 4) | ((uint64_t)((lbo & 0x3FFFF) >> 4) << 16) |
           ((uint64_t)((sbo & 0x3FFFF) >> 4) << 32) | ((uint64_t)1 << 62);
}
__device__ __forceinline__ void wgmma_m64n128(float (&d)[64], uint64_t da, uint64_t db) {
    asm volatile(
        "{\n.reg .pred p;\nsetp.ne.b32 p, 1, 0;\n"
        "wgmma.mma_async.sync.aligned.m64n128k16.f32.bf16.bf16 "
        "{%0,%1,%2,%3,%4,%5,%6,%7,%8,%9,%10,%11,%12,%13,%14,%15,"
        "%16,%17,%18,%19,%20,%21,%22,%23,%24,%25,%26,%27,%28,%29,%30,%31,"
        "%32,%33,%34,%35,%36,%37,%38,%39,%40,%41,%42,%43,%44,%45,%46,%47,"
        "%48,%49,%50,%51,%52,%53,%54,%55,%56,%57,%58,%59,%60,%61,%62,%63},"
        " %64, %65, p, 1, 1, 1, 1;\n}"
        : "+f"(d[0]), "+f"(d[1]), "+f"(d[2]), "+f"(d[3]), "+f"(d[4]), "+f"(d[5]), "+f"(d[6]), "+f"(d[7]),
          "+f"(d[8]), "+f"(d[9]), "+f"(d[10]), "+f"(d[11]), "+f"(d[12]), "+f"(d[13]), "+f"(d[14]), "+f"(d[15]),
          "+f"(d[16]), "+f"(d[17]), "+f"(d[18]), "+f"(d[19]), "+f"(d[20]), "+f"(d[21]), "+f"(d[22]), "+f"(d[23]),
          "+f"(d[24]), "+f"(d[25]), "+f"(d[26]), "+f"(d[27]), "+f"(d[28]), "+f"(d[29]), "+f"(d[30]), "+f"(d[31]),
          "+f"(d[32]), "+f"(d[33]), "+f"(d[34]), "+f"(d[35]), "+f"(d[36]), "+f"(d[37]), "+f"(d[38]), "+f"(d[39]),
          "+f"(d[40]), "+f"(d[41]), "+f"(d[42]), "+f"(d[43]), "+f"(d[44]), "+f"(d[45]), "+f"(d[46]), "+f"(d[47]),
          "+f"(d[48]), "+f"(d[49]), "+f"(d[50]), "+f"(d[51]), "+f"(d[52]), "+f"(d[53]), "+f"(d[54]), "+f"(d[55]),
          "+f"(d[56]), "+f"(d[57]), "+f"(d[58]), "+f"(d[59]), "+f"(d[60]), "+f"(d[61]), "+f"(d[62]), "+f"(d[63])
        : "l"(da), "l"(db));
}
__device__ __forceinline__ void tma_load_3d(uint32_t dst, const CUtensorMap* tm, int c0, int c1, int c2, uint32_t bar) {
    asm volatile(
        "cp.async.bulk.tensor.3d.shared::cluster.global.mbarrier::complete_tx::bytes [%0], [%1, {%3, %4, %5}], [%2];"
        ::"r"(dst), "l"(tm), "r"(bar), "r"(c0), "r"(c1), "r"(c2) : "memory");
}
__device__ __forceinline__ void tma_store_3d(const CUtensorMap* tm, uint32_t src, int c0, int c1, int c2) {
    asm volatile("cp.async.bulk.tensor.3d.global.shared::cta.bulk_group [%0, {%2, %3, %4}], [%1];"
                 ::"l"(tm), "r"(src), "r"(c0), "r"(c1), "r"(c2) : "memory");
}
template <int N>
__device__ __forceinline__ void gelu_pairs(uint32_t (&y)[N]) {
    const float k1 = -2.0f * 0.7978845608028654f * 1.4426950408889634f;
    const float k2 = k1 * 0.044715f;
    float e[2 * N], r[N];
#pragma unroll
    for (int i = 0; i < N; i++) {
        const float x0 = bf_lo(y[i]), x1 = bf_hi(y[i]);
        e[2 * i] = fminf(x0 * fmaf(k2, x0 * x0, k1), 60.f);
        e[2 * i + 1] = fminf(x1 * fmaf(k2, x1 * x1, k1), 60.f);
    }
#pragma unroll
    for (int i = 0; i < 2 * N; i++) asm volatile("ex2.approx.ftz.f32 %0, %0;" : "+f"(e[i]));
#pragma unroll
    for (int i = 0; i < N; i++) {
        e[2 * i] += 1.0f; e[2 * i + 1] += 1.0f;
        r[i] = e[2 * i] * e[2 * i + 1];
    }
#pragma unroll
    for (int i = 0; i < N; i++) asm volatile("rcp.approx.ftz.f32 %0, %0;" : "+f"(r[i]));
#pragma unroll
    for (int i = 0; i < N; i++) y[i] = pack_bf2(bf_lo(y[i]) * e[2 * i + 1] * r[i], bf_hi(y[i]) * e[2 * i] * r[i]);
}
__device__ __forceinline__ void tma_load_3d_mc(uint32_t dst, const CUtensorMap* tm, int c0, int c1, int c2, uint32_t bar, uint16_t mask) {
    asm volatile(
        "cp.async.bulk.tensor.3d.shared::cluster.global.mbarrier::complete_tx::bytes.multicast::cluster [%0], [%1, {%3, %4, %5}], [%2], %6;"
        ::"r"(dst), "l"(tm), "r"(bar), "r"(c0), "r"(c1), "r"(c2), "h"(mask) : "memory");
}
__device__ __forceinline__ void mbar_arrive_cluster(uint32_t bar, uint32_t rank) {
    asm volatile("{\n.reg .b32 ra;\nmapa.shared::cluster.u32 ra, %0, %1;\nmbarrier.arrive.shared::cluster.b64 _, [ra];\n}"
                 ::"r"(bar), "r"(rank) : "memory");
}

constexpr int G_BK = 64, G_STAGES = 8;
constexpr int G_A_BYTES = 64 * G_BK * 2, G_B_BYTES = 128 * G_BK * 2, G_STAGE_BYTES = G_A_BYTES + G_B_BYTES;
constexpr int G_OUT_BYTES = 64 * 128 * 2;
constexpr int G_SMEM = G_STAGES * G_STAGE_BYTES + G_OUT_BYTES + 1024 + 256;
constexpr int NKB1 = S_ / G_BK, NKB2 = F_ / G_BK, NT1 = (F_ / 64) * 4;

__device__ __forceinline__ void mma_kblock(float (&acc)[64], uint32_t a0) {
    asm volatile("wgmma.fence.sync.aligned;" ::: "memory");
    const uint32_t b0 = a0 + G_A_BYTES;
#pragma unroll
    for (int kk = 0; kk < G_BK / 16; kk++)
        wgmma_m64n128(acc, make_desc(a0 + kk * 2048, G_BK * 128, 1024), make_desc(b0 + kk * 2048, G_BK * 128, 1024));
    asm volatile("wgmma.commit_group.sync.aligned;" ::: "memory");
}

__global__ void __cluster_dims__(2, 1, 1) __launch_bounds__(288)
k_mlp(const __grid_constant__ CUtensorMap tmW1, const __grid_constant__ CUtensorMap tmH, const __grid_constant__ CUtensorMap tmUo,
      const __grid_constant__ CUtensorMap tmW2, const __grid_constant__ CUtensorMap tmU, const __grid_constant__ CUtensorMap tmR,
      const __grid_constant__ CUtensorMap tmO, const bf16* __restrict__ b1, const bf16* __restrict__ b2v,
      unsigned int* __restrict__ cnt TLARG) {
    TL(kid, 0);
    extern __shared__ uint8_t smem_raw[];
    uint32_t base = (smem_u32(smem_raw) + 1023) & ~1023u;
    asm volatile("" : "+r"(base));
    const uint32_t obuf = base + G_STAGES * G_STAGE_BYTES;
    const uint32_t bars = obuf + G_OUT_BYTES;
    const uint32_t rbar = bars + 16 * G_STAGES;
    const int warp = threadIdx.x >> 5, lane = threadIdx.x & 31;
    const int rank = blockIdx.x & 1, cl = blockIdx.x >> 1;
    const int mt = cl >> 1, nt = (cl & 1) * 2 + rank;
    if (blockIdx.x >= 128) {
        if (threadIdx.x == 0) {
            griddep_wait();
            griddep_launch();
            unsigned int v;
            int spin = 0;
            do {
                __nanosleep(200);
                asm volatile("ld.relaxed.gpu.global.u32 %0, [%1];" : "=r"(v) : "l"(cnt) : "memory");
            } while (v < NT1 / 4 && ++spin < 4096);
        }
        return;
    }
    const bool act1 = mt < NT1 / 4;
    const int n1 = act1 ? NKB1 : 0, total = n1 + NKB2;
    if (threadIdx.x == 0) {
        for (int i = 0; i < G_STAGES; i++) { mbar_init(bars + 8 * i, 1); mbar_init(bars + 8 * (G_STAGES + i), 8); }
        mbar_init(rbar, 1);
        asm volatile("fence.mbarrier_init.release.cluster;" ::: "memory");
    }
    __syncthreads();
    asm volatile("barrier.cluster.arrive.release.aligned;\nbarrier.cluster.wait.acquire.aligned;" ::: "memory");
    if (warp == 8) {
        if (lane == 0) {
            const uint32_t woff = rank * (G_A_BYTES / 2);
            const int krow = rank * (G_BK / 2);
            int s = 0, ph = 1;
            if (act1) {
                for (int i = 0; i < G_STAGES; i++) {
                    mbar_expect_tx(bars + 8 * i, G_STAGE_BYTES);
                    tma_load_3d_mc(base + i * G_STAGE_BYTES + woff, &tmW1, 0, i * G_BK + krow, mt, bars + 8 * i, 3);
                }
                griddep_wait();
                griddep_launch();
                TL(kid, 1);
                for (int i = 0; i < G_STAGES; i++)
                    tma_load_3d(base + i * G_STAGE_BYTES + G_A_BYTES, &tmH, 0, i * G_BK, nt * 2, bars + 8 * i);
                ph = 0;
                for (int kb = G_STAGES; kb < NKB1; kb++) {
                    mbar_wait(bars + 8 * (G_STAGES + s), ph);
                    mbar_expect_tx(bars + 8 * s, G_STAGE_BYTES);
                    tma_load_3d_mc(base + s * G_STAGE_BYTES + woff, &tmW1, 0, kb * G_BK + krow, mt, bars + 8 * s, 3);
                    tma_load_3d(base + s * G_STAGE_BYTES + G_A_BYTES, &tmH, 0, kb * G_BK, nt * 2, bars + 8 * s);
                    if (++s == G_STAGES) { s = 0; ph ^= 1; }
                }
            }
            for (int i = 0; i < G_STAGES; i++) {
                mbar_wait(bars + 8 * (G_STAGES + i), ph);
                mbar_expect_tx(bars + 8 * i, G_STAGE_BYTES);
                tma_load_3d_mc(base + i * G_STAGE_BYTES + woff, &tmW2, 0, i * G_BK + krow, mt, bars + 8 * i, 3);
            }
            if (!act1) {
                griddep_wait();
                griddep_launch();
                mbar_expect_tx(rbar, G_OUT_BYTES);
                tma_load_3d(obuf, &tmR, 0, mt * 64, nt * 2, rbar);
            }
            ph ^= 1;
            {
                unsigned int v;
                int spin = 0;
                do {
                    asm volatile("ld.relaxed.gpu.global.u32 %0, [%1];" : "=r"(v) : "l"(cnt + nt * 32) : "memory");
                } while (v < NT1 / 4 && ++spin < (1 << 21));
                asm volatile("fence.proxy.async;" ::: "memory");
            }
            TL(kid, 8);
            for (int i = 0; i < G_STAGES; i++)
                tma_load_3d(base + i * G_STAGE_BYTES + G_A_BYTES, &tmU, 0, i * G_BK, nt * 2, bars + 8 * i);
            for (int kb = G_STAGES; kb < NKB2; kb++) {
                mbar_wait(bars + 8 * (G_STAGES + s), ph);
                mbar_expect_tx(bars + 8 * s, G_STAGE_BYTES);
                tma_load_3d_mc(base + s * G_STAGE_BYTES + woff, &tmW2, 0, kb * G_BK + krow, mt, bars + 8 * s, 3);
                tma_load_3d(base + s * G_STAGE_BYTES + G_A_BYTES, &tmU, 0, kb * G_BK, nt * 2, bars + 8 * s);
                if (++s == G_STAGES) { s = 0; ph ^= 1; }
            }
        }
    } else {
        const int g = lane >> 2;
        const int mrow = (warp & 3) * 16 + (lane & 7) + (lane & 8);
        const uint32_t rowa = obuf + mrow * 128;
        float acc[64];
        int s = 0, ph = 0;
        if (act1) {
            if (warp < 4) {
                uint32_t bb[2];
#pragma unroll
                for (int h = 0; h < 2; h++) {
                    float bv = __bfloat162float(b1[mt * 64 + warp * 16 + g + 8 * h]);
                    bb[h] = pack_bf2(bv, bv);
                }
#pragma unroll
                for (int i = 0; i < 64; i++) acc[i] = 0.f;
                griddep_wait();
#pragma unroll 1
                for (int kb = 0; kb < NKB1; kb++) {
                    mbar_wait(bars + 8 * s, ph);
                    mma_kblock(acc, base + s * G_STAGE_BYTES);
                    asm volatile("wgmma.wait_group.sync.aligned 1;" ::: "memory");
                    if (kb > 0 && lane < 2) mbar_arrive_cluster(bars + 8 * (G_STAGES + (s == 0 ? G_STAGES - 1 : s - 1)), lane);
                    if (++s == G_STAGES) { s = 0; ph ^= 1; }
                }
                asm volatile("wgmma.wait_group.sync.aligned 0;" ::: "memory");
                if (lane < 2) mbar_arrive_cluster(bars + 8 * (2 * G_STAGES - 1), lane);
                TL(kid, 3);
#pragma unroll
                for (int i2 = 0; i2 < 8; i2++) {
                    const uint32_t ad = rowa + (i2 >> 2) * 8192 + (((2 * (i2 & 3) + (lane >> 4)) ^ (lane & 7)) << 4);
                    uint32_t y[4];
#pragma unroll
                    for (int q = 0; q < 4; q++) y[q] = bf2_add(pack_bf2(acc[8 * i2 + 2 * q], acc[8 * i2 + 2 * q + 1]), bb[q & 1]);
                    asm volatile("stmatrix.sync.aligned.m8n8.x4.shared.b16 [%0], {%1,%2,%3,%4};"
                                 ::"r"(ad), "r"(y[0]), "r"(y[1]), "r"(y[2]), "r"(y[3]) : "memory");
                }
            }
            asm volatile("bar.sync 1, 256;" ::: "memory");
            {
                uint32_t y[16];
#pragma unroll
                for (int i = 0; i < 4; i++)
                    asm volatile("ld.shared.v4.b32 {%0,%1,%2,%3}, [%4];" : "=r"(y[4 * i]), "=r"(y[4 * i + 1]), "=r"(y[4 * i + 2]), "=r"(y[4 * i + 3])
                                 : "r"(obuf + (threadIdx.x + 256 * i) * 16));
                gelu_pairs<16>(y);
#pragma unroll
                for (int i = 0; i < 4; i++)
                    asm volatile("st.shared.v4.b32 [%0], {%1,%2,%3,%4};" ::"r"(obuf + (threadIdx.x + 256 * i) * 16),
                                 "r"(y[4 * i]), "r"(y[4 * i + 1]), "r"(y[4 * i + 2]), "r"(y[4 * i + 3]) : "memory");
            }
            asm volatile("fence.proxy.async.shared::cta;" ::: "memory");
            asm volatile("bar.sync 1, 256;" ::: "memory");
            TL(kid, 4);
            if (threadIdx.x == 128) {
                tma_store_3d(&tmUo, obuf, 0, mt * 64, nt * 2);
                asm volatile("cp.async.bulk.commit_group;" ::: "memory");
                asm volatile("cp.async.bulk.wait_group 0;" ::: "memory");
                asm volatile("red.relaxed.gpu.global.add.u32 [%0], 1;" ::"l"(cnt + nt * 32) : "memory");
                TL(kid, 11);
                mbar_expect_tx(rbar, G_OUT_BYTES);
                tma_load_3d(obuf, &tmR, 0, mt * 64, nt * 2, rbar);
            }
        }
        if (warp < 4) {
            uint32_t bb[2];
#pragma unroll
            for (int h = 0; h < 2; h++) {
                float bv = __bfloat162float(b2v[mt * 64 + warp * 16 + g + 8 * h]);
                bb[h] = pack_bf2(bv, bv);
            }
#pragma unroll
            for (int i = 0; i < 64; i++) acc[i] = 0.f;
            if (!act1) griddep_wait();
#pragma unroll 1
            for (int kb = 0; kb < NKB2; kb++) {
                mbar_wait(bars + 8 * s, ph);
                if (kb == 0) TL(kid, 9);
                mma_kblock(acc, base + s * G_STAGE_BYTES);
                asm volatile("wgmma.wait_group.sync.aligned 1;" ::: "memory");
                if (kb > 0 && kb <= NKB2 - G_STAGES && lane < 2)
                    mbar_arrive_cluster(bars + 8 * (G_STAGES + (s == 0 ? G_STAGES - 1 : s - 1)), lane);
                if (++s == G_STAGES) { s = 0; ph ^= 1; }
            }
            asm volatile("wgmma.wait_group.sync.aligned 0;" ::: "memory");
            TL(kid, 5);
            mbar_wait(rbar, 0);
#pragma unroll
            for (int c = 0; c < 2; c++) {
#pragma unroll
                for (int i2 = 0; i2 < 4; i2++) {
                    const uint32_t ad = rowa + c * 8192 + (((2 * i2 + (lane >> 4)) ^ (lane & 7)) << 4);
                    uint32_t r[4];
                    asm volatile("ldmatrix.sync.aligned.m8n8.x4.shared.b16 {%0,%1,%2,%3}, [%4];"
                                 : "=r"(r[0]), "=r"(r[1]), "=r"(r[2]), "=r"(r[3]) : "r"(ad));
#pragma unroll
                    for (int q = 0; q < 4; q++)
                        r[q] = bf2_add(r[q], bf2_add(pack_bf2(acc[32 * c + 8 * i2 + 2 * q], acc[32 * c + 8 * i2 + 2 * q + 1]), bb[q & 1]));
                    asm volatile("stmatrix.sync.aligned.m8n8.x4.shared.b16 [%0], {%1,%2,%3,%4};"
                                 ::"r"(ad), "r"(r[0]), "r"(r[1]), "r"(r[2]), "r"(r[3]) : "memory");
                }
                asm volatile("fence.proxy.async.shared::cta;" ::: "memory");
                asm volatile("bar.sync 2, 128;" ::: "memory");
                if (threadIdx.x == 0) {
                    tma_store_3d(&tmO, obuf + c * 8192, 0, mt * 64, nt * 2 + c);
                    asm volatile("cp.async.bulk.commit_group;" ::: "memory");
                }
            }
            if (threadIdx.x == 0) asm volatile("cp.async.bulk.wait_group.read 0;" ::: "memory");
            TL(kid, 2);
        }
    }
    (void)total;
}

typedef CUresult (*EncodeFn)(CUtensorMap*, CUtensorMapDataType, cuuint32_t, void*, const cuuint64_t*, const cuuint64_t*,
                             const cuuint32_t*, const cuuint32_t*, CUtensorMapInterleave, CUtensorMapSwizzle,
                             CUtensorMapL2promotion, CUtensorMapFloatOOBfill);

void make_map(EncodeFn fn, CUtensorMap* tm, const void* ptr, int R, int C, int rows, int nchunk) {
    cuuint64_t dims[3] = {64, (cuuint64_t)R, (cuuint64_t)(C / 64)};
    cuuint64_t strides[2] = {(cuuint64_t)C * 2, 128};
    cuuint32_t box[3] = {64, (cuuint32_t)rows, (cuuint32_t)nchunk};
    cuuint32_t es[3] = {1, 1, 1};
    fn(tm, CU_TENSOR_MAP_DATA_TYPE_BFLOAT16, 3, (void*)ptr, dims, strides, box, es, CU_TENSOR_MAP_INTERLEAVE_NONE,
       CU_TENSOR_MAP_SWIZZLE_128B, CU_TENSOR_MAP_L2_PROMOTION_L2_256B, CU_TENSOR_MAP_FLOAT_OOB_FILL_NONE);
}

template <typename... KArgs, typename... Args>
void launch(void (*kern)(KArgs...), int grid, int block, int smem, bool pdl, Args... args) {
    cudaLaunchConfig_t cfg = {};
    cfg.gridDim = dim3(grid); cfg.blockDim = dim3(block); cfg.dynamicSmemBytes = smem; cfg.stream = cudaStreamPerThread;
    cudaLaunchAttribute at[1];
    at[0].id = cudaLaunchAttributeProgrammaticStreamSerialization;
    at[0].val.programmaticStreamSerializationAllowed = 1;
    cfg.attrs = at; cfg.numAttrs = pdl ? 1 : 0;
    cudaLaunchKernelEx(&cfg, kern, KArgs(args)...);
}

}

extern "C" void kernel_launch(void* const* d_in, const int* in_sizes, int n_in, void* d_out, int out_size) {
    const bf16* x = (const bf16*)d_in[0];
    const bf16* wr = (const bf16*)d_in[1];
    const bf16* wi = (const bf16*)d_in[2];
    const bf16* w1 = (const bf16*)d_in[4];
    const bf16* b1 = (const bf16*)d_in[5];
    const bf16* w2 = (const bf16*)d_in[6];
    const bf16* b2 = (const bf16*)d_in[7];
    bf16* out = (bf16*)d_out;

    static EncodeFn enc = nullptr;
    static bf16 *p_x1, *p_h, *p_u, *p_x2;
    static unsigned int* p_cnt;
    if (!enc) {
        cudaDriverEntryPointQueryResult qr;
        void* fn = nullptr;
        cudaGetDriverEntryPoint("cuTensorMapEncodeTiled", &fn, cudaEnableDefault, &qr);
        enc = (EncodeFn)fn;
        cudaGetSymbolAddress((void**)&p_x1, g_x1);
        cudaGetSymbolAddress((void**)&p_h, g_h);
        cudaGetSymbolAddress((void**)&p_u, g_u);
        cudaGetSymbolAddress((void**)&p_x2, g_x2);
        cudaGetSymbolAddress((void**)&p_cnt, g_cnt);
        cudaFuncSetAttribute(k_mlp, cudaFuncAttributeMaxDynamicSharedMemorySize, G_SMEM);
        cudaFuncSetAttribute(k_p1, cudaFuncAttributeMaxDynamicSharedMemorySize, WP_SMEM);
        const int co = cudaSharedmemCarveoutMaxShared;
        cudaFuncSetAttribute(k_mlp, cudaFuncAttributePreferredSharedMemoryCarveout, co);
        cudaFuncSetAttribute(k_p1, cudaFuncAttributePreferredSharedMemoryCarveout, co);
        cudaFuncSetAttribute(k_p2<false>, cudaFuncAttributePreferredSharedMemoryCarveout, co);
        cudaFuncSetAttribute(k_p2<true>, cudaFuncAttributePreferredSharedMemoryCarveout, co);
        cudaFuncSetAttribute(k_p3, cudaFuncAttributePreferredSharedMemoryCarveout, co);
    }
    CUtensorMap tmW1, tmW2, tmH, tmU, tmUo, tmX1, tmX2, tmOut;
    make_map(enc, &tmW1, w1, S_, F_, G_BK / 2, 1);
    make_map(enc, &tmW2, w2, F_, S_, G_BK / 2, 1);
    make_map(enc, &tmH, p_h, S_, D_, G_BK, 2);
    make_map(enc, &tmU, p_u, F_, D_, G_BK, 2);
    make_map(enc, &tmUo, p_u, F_, D_, 64, 2);
    make_map(enc, &tmX1, p_x1, S_, D_, 64, 2);
    make_map(enc, &tmX2, p_x2, S_, D_, 64, 1);
    make_map(enc, &tmOut, out, S_, D_, 64, 1);

    for (int layer = 0; layer < 2; layer++) {
        const bf16* xin = layer == 0 ? x : p_x2;
        if (layer == 0) {
            launch(k_p1, 192, 512, WP_SMEM, false, xin, wr, wi TLPASS(0));
            launch(k_p2<false>, 132, 256, 0, true, (const uint8_t*)w1, S_ * F_ * 2 / 128 TLPASS(1));
        } else {
            launch(k_p1, 128, 512, P1_SMEM, true, xin, wr, wi TLPASS(5));
            launch(k_p2<true>, 132, 256, 0, true, (const uint8_t*)w1, 0 TLPASS(6));
        }
        launch(k_p3, 128, 512, 0, true, xin, p_cnt + 128 * layer, (const uint8_t*)w2, layer == 0 ? S_ * F_ * 2 / 128 : 0 TLPASS(layer * 5 + 2));
        launch(k_mlp, 132, 288, G_SMEM, true, tmW1, tmH, tmUo, tmW2, tmU, tmX1, layer == 0 ? tmX2 : tmOut, b1, b2,
               p_cnt + 128 * layer TLPASS(layer * 5 + 3));
    }
}
```
